```python
import torch

def _softmax(x, axis=-1):
    return torch.softmax(x, dim=axis)

def _gelu(x):
    return torch.nn.functional.gelu(x, approximate='tanh')

def _silu(x):
    return torch.nn.functional.silu(x)

def _sigmoid(x):
    return torch.sigmoid(x)

def _layernorm(x, axis=-1, eps=1e-05):
    m = x.mean(dim=axis, keepdim=True)
    v = x.var(dim=axis, keepdim=True, unbiased=False)
    return (x - m) / torch.sqrt(v + eps)

def _scatter_add(tgt, idx, src, axis=0):
    return tgt.clone().index_add_(axis, idx, src)

def _segment_sum(src, seg, n):
    out = torch.zeros((n,) + src.shape[1:], dtype=src.dtype)
    return out.index_add_(0, seg, src)

def _pad(x, pw):
    flat = tuple((v for pair in reversed(pw) for v in pair))
    return torch.nn.functional.pad(x, flat)
kernel_name = 'gated_mix__memory_aug_recurrent_mem_tr__glu_gated_glu__prompt'

def setup_inputs():

    _w = lambda a: (lambda t: t.to(torch.bfloat16) if t.is_floating_point() else t)(torch.as_tensor(a))

    def _A_setup():
        B, S, Dm = (1, 2048, 512)
        H, Dh = (32, 128)
        M, seg = (8, 32)
        seg = min(seg, S)
        S = S // seg * seg
        return {'x': _w((lambda *s: torch.randn(*s, dtype=torch.bfloat16) * 0.05)(B, S, Dm)), 'mem0': _w((lambda *s: torch.randn(*s, dtype=torch.bfloat16) * 0.8)(B, M, Dm)), 'Wq': _w((lambda *s: torch.randn(*s, dtype=torch.bfloat16) * 1.6)(Dm, H, Dh) * Dm ** (-0.5)), 'Wk': _w((lambda *s: torch.randn(*s, dtype=torch.bfloat16) * 1.6)(Dm, H, Dh) * Dm ** (-0.5)), 'Wv': _w((lambda *s: torch.randn(*s, dtype=torch.bfloat16) * 0.8)(Dm, H, Dh) * Dm ** (-0.5)), 'Wo': _w((lambda *s: torch.randn(*s, dtype=torch.bfloat16) * 0.8)(H, Dh, Dm) * (H * Dh) ** (-0.5)), 'seg_len': seg}
    _A_in = _A_setup()

    def _B_setup():
        B, S, D, F = (1, 2048, 512, 1792)
        return {'x': _w((lambda *s: torch.randn(*s, dtype=torch.bfloat16) * 0.05)(B, S, D)), 'w_gate': _w((lambda *s: torch.randn(*s, dtype=torch.bfloat16) * 0.4)(D, F)), 'w_up': _w((lambda *s: torch.randn(*s, dtype=torch.bfloat16) * 0.05)(D, F)), 'w_down': _w((lambda *s: torch.randn(*s, dtype=torch.bfloat16) * 0.05)(F, D))}
    _B_in = _B_setup()
    return {'A_x': _A_in['x'], 'A_mem0': _A_in['mem0'], 'A_Wq': _A_in['Wq'], 'A_Wk': _A_in['Wk'], 'A_Wv': _A_in['Wv'], 'A_Wo': _A_in['Wo'], 'A_seg_len': _A_in['seg_len'], 'B_x': _B_in['x'], 'B_w_gate': _B_in['w_gate'], 'B_w_up': _B_in['w_up'], 'B_w_down': _B_in['w_down'], 'gate_w': _w((lambda *s: torch.randn(*s, dtype=torch.bfloat16) * 0.05)(512) * 16.0)}

def reference(A_x, A_mem0, A_Wq, A_Wk, A_Wv, A_Wo, A_seg_len, B_x, B_w_gate, B_w_up, B_w_down, gate_w):

    def _A_ref(x, mem0, Wq, Wk, Wv, Wo, seg_len):
        B, S, Dm = x.shape
        H, Dh = (Wq.shape[1], Wq.shape[2])
        M = mem0.shape[1]
        scale = Dh ** (-0.5)
        n_seg = S // seg_len
        L = M + seg_len
        idx = torch.arange(L)
        mask = (idx[:, None] < M) | (idx[:, None] >= idx[None, :])
        mem = mem0
        outs = []
        for s in range(n_seg):
            xs = x[:, s * seg_len:(s + 1) * seg_len, :].clone()
            h = torch.concatenate([mem, xs], axis=1)
            q = torch.einsum('btd,dhe->bhte', h, Wq)
            k = torch.einsum('btd,dhe->bhte', h, Wk)
            v = torch.einsum('btd,dhe->bhte', h, Wv)
            scores = torch.einsum('bhqe,bhke->bhqk', q, k) * scale
            scores = torch.where(mask[None, None], scores, -1000000000.0)
            p = _softmax(scores, axis=-1)
            o = torch.einsum('bhqk,bhke->bhqe', p, v)
            o = torch.einsum('bhte,hed->btd', o, Wo)
            mem = o[:, :M, :].clone()
            outs.append(o[:, M:, :])
        return torch.concatenate(outs, axis=1)

    def _B_ref(x, w_gate, w_up, w_down):
        g = torch.einsum('bsd,df->bsf', x, w_gate)
        u = torch.einsum('bsd,df->bsf', x, w_up)
        h = _sigmoid(g) * u
        return torch.einsum('bsf,fd->bsd', h, w_down)
    x = A_x
    g = _sigmoid((x * gate_w).sum(-1, keepdims=True))
    a = _A_ref(x, A_mem0, A_Wq, A_Wk, A_Wv, A_Wo, A_seg_len)
    b = _B_ref(x, B_w_gate, B_w_up, B_w_down)
    return g * a + (1 - g) * b
```

```cpp
#include <cuda_runtime.h>
#include <cuda_bf16.h>
#include <cuda.h>
#include <stdint.h>

typedef __nv_bfloat16 bf16;

constexpr int kS = 2048, kD = 512, kH = 32, kF = 1792, kNSeg = 64;

__device__ __align__(8192) unsigned char g_mail[128 * 4096];
__device__ __align__(8192) unsigned char g_pub[63 * 2 * 8192];
__device__ __align__(1024) bf16 g_o[(size_t)kS * 4096];
__device__ __align__(1024) bf16 g_hid[kS * kF];
__device__ __align__(16) float g_acc[14 * 128 * 256];
__device__ float g_gate[kS];
__device__ unsigned g_ticket;
constexpr int C_HID = 0, C_O = 16, C_F2 = 32, C_ARR = 64, C_DONE = 320;
__device__ unsigned g_cnt[576];

#define TMARKD(cond, ev, dep)
#define OPAQUE(v_) v_ = __shfl_xor_sync(~0u, v_, 0)

__device__ __forceinline__ uint32_t smem_u32(const void* p) { return (uint32_t)__cvta_generic_to_shared(p); }
__device__ __forceinline__ void mbar_init(uint32_t a, uint32_t n) { asm volatile("mbarrier.init.shared::cta.b64 [%0], %1;" ::"r"(a), "r"(n) : "memory"); }
__device__ __forceinline__ void mbar_arrive(uint32_t a) { asm volatile("mbarrier.arrive.shared::cta.b64 _, [%0];" ::"r"(a) : "memory"); }
__device__ __forceinline__ void mbar_arrive_tx(uint32_t a, uint32_t b) { asm volatile("mbarrier.arrive.expect_tx.shared::cta.b64 _, [%0], %1;" ::"r"(a), "r"(b) : "memory"); }
__device__ __forceinline__ void mbar_arrive_remote(uint32_t a) { asm volatile("mbarrier.arrive.release.cluster.shared::cluster.b64 _, [%0];" ::"r"(a) : "memory"); }
__device__ __forceinline__ bool mbar_try(uint32_t a, uint32_t par) {
  uint32_t ok;
  asm volatile("{.reg .pred p; mbarrier.try_wait.parity.shared::cta.b64 p, [%1], %2; selp.u32 %0, 1, 0, p;}" : "=r"(ok) : "r"(a), "r"(par) : "memory");
  return ok;
}
__device__ __forceinline__ bool mbar_try_cl(uint32_t a, uint32_t par) {
  uint32_t ok;
  asm volatile("{.reg .pred p; mbarrier.try_wait.parity.acquire.cluster.shared::cta.b64 p, [%1], %2; selp.u32 %0, 1, 0, p;}" : "=r"(ok) : "r"(a), "r"(par) : "memory");
  return ok;
}
__device__ __forceinline__ void spend(int& budget) { asm volatile("{.reg .pred p; .reg .u64 z; mov.u64 z, 0; add.s32 %0, %0, -1; setp.lt.s32 p, %0, 0; @p st.global.u32 [z], %0;}" : "+r"(budget)); }
__device__ __forceinline__ void mbar_wait(uint32_t a, uint32_t par, int& budget) { while (!mbar_try(a, par)) { spend(budget); } }
__device__ __forceinline__ void mbar_wait_cl(uint32_t a, uint32_t par, int& budget) { while (!mbar_try_cl(a, par)) { spend(budget); } }
__device__ __forceinline__ uint32_t mapa(uint32_t a, uint32_t r) { uint32_t o; asm("mapa.shared::cluster.u32 %0, %1, %2;" : "=r"(o) : "r"(a), "r"(r)); return o; }
__device__ __forceinline__ void fence_async_smem() { asm volatile("fence.proxy.async.shared::cta;" ::: "memory"); }
__device__ __forceinline__ void bar_sync(int id, int n) { asm volatile("bar.sync %0, %1;" ::"r"(id), "r"(n) : "memory"); }
__device__ __forceinline__ void bar_arrive(int id, int n) { asm volatile("bar.arrive %0, %1;" ::"r"(id), "r"(n) : "memory"); }
__device__ __forceinline__ void cluster_sync_all() {
  asm volatile("barrier.cluster.arrive.release.aligned; barrier.cluster.wait.acquire.aligned;" ::: "memory");
}
__device__ __forceinline__ void tma_2d(uint32_t dst, const CUtensorMap* tm, int c0, int c1, uint32_t bar) {
  asm volatile("cp.async.bulk.tensor.2d.shared::cluster.global.mbarrier::complete_tx::bytes [%0], [%1, {%3, %4}], [%2];"
               ::"r"(dst), "l"(tm), "r"(bar), "r"(c0), "r"(c1) : "memory");
}
__device__ __forceinline__ void tma_3d(uint32_t dst, const CUtensorMap* tm, int c0, int c1, int c2, uint32_t bar) {
  asm volatile("cp.async.bulk.tensor.3d.shared::cluster.global.mbarrier::complete_tx::bytes [%0], [%1, {%3, %4, %5}], [%2];"
               ::"r"(dst), "l"(tm), "r"(bar), "r"(c0), "r"(c1), "r"(c2) : "memory");
}
__device__ __forceinline__ void bulk_s2c(uint32_t dst, uint32_t src, uint32_t bytes, uint32_t bar) {
  asm volatile("cp.async.bulk.shared::cluster.shared::cta.mbarrier::complete_tx::bytes [%0], [%1], %2, [%3];"
               ::"r"(dst), "r"(src), "r"(bytes), "r"(bar) : "memory");
}
__device__ __forceinline__ void bulk_s2g(void* dst, uint32_t src, uint32_t bytes) {
  asm volatile("cp.async.bulk.global.shared::cta.bulk_group [%0], [%1], %2;" ::"l"(dst), "r"(src), "r"(bytes) : "memory");
}
__device__ __forceinline__ void st_async32(uint32_t dst, uint32_t v, uint32_t bar) {
  asm volatile("st.async.weak.shared::cluster.mbarrier::complete_tx::bytes.b32 [%0], %1, [%2];" ::"r"(dst), "r"(v), "r"(bar) : "memory");
}
__device__ __forceinline__ void ldsm4(uint32_t a, uint32_t& r0, uint32_t& r1, uint32_t& r2, uint32_t& r3) {
  asm volatile("ldmatrix.sync.aligned.m8n8.x4.shared.b16 {%0,%1,%2,%3}, [%4];" : "=r"(r0), "=r"(r1), "=r"(r2), "=r"(r3) : "r"(a) : "memory");
}
__device__ __forceinline__ void ldsm4t(uint32_t a, uint32_t& r0, uint32_t& r1, uint32_t& r2, uint32_t& r3) {
  asm volatile("ldmatrix.sync.aligned.m8n8.x4.trans.shared.b16 {%0,%1,%2,%3}, [%4];" : "=r"(r0), "=r"(r1), "=r"(r2), "=r"(r3) : "r"(a) : "memory");
}
__device__ __forceinline__ void stsm4(uint32_t a, uint32_t r0, uint32_t r1, uint32_t r2, uint32_t r3) {
  asm volatile("stmatrix.sync.aligned.m8n8.x4.shared.b16 [%0], {%1,%2,%3,%4};" ::"r"(a), "r"(r0), "r"(r1), "r"(r2), "r"(r3) : "memory");
}
__device__ __forceinline__ void stsm2(uint32_t a, uint32_t r0, uint32_t r1) {
  asm volatile("stmatrix.sync.aligned.m8n8.x2.shared.b16 [%0], {%1,%2};" ::"r"(a), "r"(r0), "r"(r1) : "memory");
}
__device__ __forceinline__ void stsm4t(uint32_t a, uint32_t r0, uint32_t r1, uint32_t r2, uint32_t r3) {
  asm volatile("stmatrix.sync.aligned.m8n8.x4.trans.shared.b16 [%0], {%1,%2,%3,%4};" ::"r"(a), "r"(r0), "r"(r1), "r"(r2), "r"(r3) : "memory");
}
__device__ __forceinline__ void mma16z(float (&c)[4], uint32_t a0, uint32_t a1, uint32_t a2, uint32_t a3, uint32_t b0, uint32_t b1) {
  asm volatile("mma.sync.aligned.m16n8k16.row.col.f32.bf16.bf16.f32 {%0,%1,%2,%3}, {%4,%5,%6,%7}, {%8,%9}, {%10,%10,%10,%10};"
               : "=f"(c[0]), "=f"(c[1]), "=f"(c[2]), "=f"(c[3]) : "r"(a0), "r"(a1), "r"(a2), "r"(a3), "r"(b0), "r"(b1), "f"(0.f));
}
__device__ __forceinline__ void mma16(float (&c)[4], uint32_t a0, uint32_t a1, uint32_t a2, uint32_t a3, uint32_t b0, uint32_t b1) {
  asm volatile("mma.sync.aligned.m16n8k16.row.col.f32.bf16.bf16.f32 {%0,%1,%2,%3}, {%4,%5,%6,%7}, {%8,%9}, {%0,%1,%2,%3};"
               : "+f"(c[0]), "+f"(c[1]), "+f"(c[2]), "+f"(c[3]) : "r"(a0), "r"(a1), "r"(a2), "r"(a3), "r"(b0), "r"(b1));
}
__device__ __forceinline__ void mma8(float (&c)[4], uint32_t a0, uint32_t a1, uint32_t b0) {
  asm volatile("mma.sync.aligned.m16n8k8.row.col.f32.bf16.bf16.f32 {%0,%1,%2,%3}, {%4,%5}, {%6}, {%0,%1,%2,%3};"
               : "+f"(c[0]), "+f"(c[1]), "+f"(c[2]), "+f"(c[3]) : "r"(a0), "r"(a1), "r"(b0));
}
__device__ __forceinline__ uint32_t pack2(float lo, float hi) {
  uint32_t r; asm("cvt.rn.bf16x2.f32 %0, %1, %2;" : "=r"(r) : "f"(hi), "f"(lo)); return r;
}
__device__ __forceinline__ float ex2(float x) { float r; asm("ex2.approx.ftz.f32 %0, %1;" : "=f"(r) : "f"(x)); return r; }
__device__ __forceinline__ void wg_fence() { asm volatile("wgmma.fence.sync.aligned;" ::: "memory"); }
__device__ __forceinline__ void wg_commit() { asm volatile("wgmma.commit_group.sync.aligned;" ::: "memory"); }
template <int N> __device__ __forceinline__ void wg_wait() { asm volatile("wgmma.wait_group.sync.aligned %0;" ::"n"(N) : "memory"); }
template <int TB>
__device__ __forceinline__ void wgmma_rs32(float (&d)[16], uint32_t a0, uint32_t a1, uint32_t a2, uint32_t a3, uint64_t desc, int acc) {
  asm volatile("{.reg .pred p; setp.ne.b32 p, %21, 0;\n"
               "wgmma.mma_async.sync.aligned.m64n32k16.f32.bf16.bf16 {%0,%1,%2,%3,%4,%5,%6,%7,%8,%9,%10,%11,%12,%13,%14,%15}, {%16,%17,%18,%19}, %20, p, 1, 1, %22;}"
               : "+f"(d[0]), "+f"(d[1]), "+f"(d[2]), "+f"(d[3]), "+f"(d[4]), "+f"(d[5]), "+f"(d[6]), "+f"(d[7]),
                 "+f"(d[8]), "+f"(d[9]), "+f"(d[10]), "+f"(d[11]), "+f"(d[12]), "+f"(d[13]), "+f"(d[14]), "+f"(d[15])
               : "r"(a0), "r"(a1), "r"(a2), "r"(a3), "l"(desc), "r"(acc), "n"(TB));
}
template <int TA, int TB>
__device__ __forceinline__ void wgmma_ss32(float (&d)[16], uint64_t adesc, uint64_t desc, int acc) {
  asm volatile("{.reg .pred p; setp.ne.b32 p, %18, 0;\n"
               "wgmma.mma_async.sync.aligned.m64n32k16.f32.bf16.bf16 {%0,%1,%2,%3,%4,%5,%6,%7,%8,%9,%10,%11,%12,%13,%14,%15}, %16, %17, p, 1, 1, %19, %20;}"
               : "+f"(d[0]), "+f"(d[1]), "+f"(d[2]), "+f"(d[3]), "+f"(d[4]), "+f"(d[5]), "+f"(d[6]), "+f"(d[7]),
                 "+f"(d[8]), "+f"(d[9]), "+f"(d[10]), "+f"(d[11]), "+f"(d[12]), "+f"(d[13]), "+f"(d[14]), "+f"(d[15])
               : "l"(adesc), "l"(desc), "r"(acc), "n"(TA), "n"(TB));
}
__device__ __forceinline__ void wgmma_ss40_tt(float (&d)[20], uint64_t adesc, uint64_t desc, int acc) {
  asm volatile("{.reg .pred p; setp.ne.b32 p, %22, 0;\n"
               "wgmma.mma_async.sync.aligned.m64n40k16.f32.bf16.bf16 {%0,%1,%2,%3,%4,%5,%6,%7,%8,%9,%10,%11,%12,%13,%14,%15,%16,%17,%18,%19}, %20, %21, p, 1, 1, 1, 1;}"
               : "+f"(d[0]), "+f"(d[1]), "+f"(d[2]), "+f"(d[3]), "+f"(d[4]), "+f"(d[5]), "+f"(d[6]), "+f"(d[7]),
                 "+f"(d[8]), "+f"(d[9]), "+f"(d[10]), "+f"(d[11]), "+f"(d[12]), "+f"(d[13]), "+f"(d[14]), "+f"(d[15]),
                 "+f"(d[16]), "+f"(d[17]), "+f"(d[18]), "+f"(d[19])
               : "l"(adesc), "l"(desc), "r"(acc));
}
__device__ __forceinline__ float rcp(float x) { float r; asm("rcp.approx.ftz.f32 %0, %1;" : "=f"(r) : "f"(x)); return r; }
__device__ __forceinline__ uint64_t make_desc(uint32_t addr, uint32_t lbo, uint32_t sbo, uint32_t swz) {
  return (uint64_t)((addr & 0x3FFFF) >> 4) | ((uint64_t)(lbo >> 4) << 16) | ((uint64_t)(sbo >> 4) << 32) | ((uint64_t)swz << 62);
}
__device__ __forceinline__ void ld_b128(const void* p, uint32_t& a, uint32_t& b, uint32_t& c, uint32_t& d) {
  asm volatile("{.reg .b128 t; .reg .b64 lo, hi; ld.relaxed.gpu.global.b128 t, [%4]; mov.b128 {lo, hi}, t; mov.b64 {%0,%1}, lo; mov.b64 {%2,%3}, hi;}"
               : "=r"(a), "=r"(b), "=r"(c), "=r"(d) : "l"(p) : "memory");
}
__device__ __forceinline__ void st_b128(void* p, uint32_t a, uint32_t b, uint32_t c, uint32_t d) {
  asm volatile("{.reg .b128 t; .reg .b64 lo, hi; mov.b64 lo, {%1,%2}; mov.b64 hi, {%3,%4}; mov.b128 t, {lo, hi}; st.relaxed.gpu.global.b128 [%0], t;}"
               ::"l"(p), "r"(a), "r"(b), "r"(c), "r"(d) : "memory");
}
__device__ __forceinline__ void ld_v4(const void* p, uint32_t& a, uint32_t& b, uint32_t& c, uint32_t& d) {
  asm volatile("ld.relaxed.gpu.global.v4.u32 {%0,%1,%2,%3}, [%4];" : "=r"(a), "=r"(b), "=r"(c), "=r"(d) : "l"(p) : "memory");
}
__device__ __forceinline__ void st_u32(void* p, uint32_t v) { asm volatile("st.relaxed.gpu.global.u32 [%0], %1;" ::"l"(p), "r"(v) : "memory"); }
__device__ __forceinline__ void sts128(uint32_t a, uint32_t x, uint32_t y, uint32_t z, uint32_t w) {
  asm volatile("st.shared.v4.u32 [%0], {%1,%2,%3,%4};" ::"r"(a), "r"(x), "r"(y), "r"(z), "r"(w) : "memory");
}
__device__ __forceinline__ void lds128f(uint32_t a, float& x, float& y, float& z, float& w) {
  asm volatile("ld.shared.v4.f32 {%0,%1,%2,%3}, [%4];" : "=f"(x), "=f"(y), "=f"(z), "=f"(w) : "r"(a) : "memory");
}
__device__ __forceinline__ void sts32f(uint32_t a, float x) { asm volatile("st.shared.f32 [%0], %1;" ::"r"(a), "f"(x) : "memory"); }
__device__ __forceinline__ void lds64f(uint32_t a, float& x, float& y) { asm volatile("ld.shared.v2.f32 {%0,%1}, [%2];" : "=f"(x), "=f"(y) : "r"(a) : "memory"); }

#define K_SPLIT 7
#define POLL_DELAY 0
#define RED_DELAY 0
namespace rk {
constexpr uint32_t XT = 0;
constexpr uint32_t RA = 65536;
constexpr uint32_t KV = RA;
constexpr uint32_t QX = KV + 4 * 20480;
constexpr uint32_t WRES = RA + 14 * 8192;
constexpr uint32_t WOS = RA + 131072;
constexpr uint32_t OST = WOS;
constexpr uint32_t PS = WOS + 8192;
constexpr uint32_t MEMS = WOS + 16384;
constexpr uint32_t QM = MEMS + 8192;
constexpr uint32_t SC = QM + 2048;
constexpr uint32_t BAR = SC + 2048;
constexpr uint32_t B_QKV = BAR;
constexpr uint32_t B_KV = BAR + 8;
constexpr uint32_t B_XF = BAR + 40;
constexpr uint32_t B_W = BAR + 56;
constexpr uint32_t B_FREE = BAR + 88;
constexpr uint32_t TM = BAR + 256;
constexpr uint32_t SMEM = TM + 4096 + 1024;
constexpr int NB_P = 1, NB_T = 2, NB_MEM = 3, NB_S = 4, NB_TD = 5, NB_PUB = 6;
constexpr float kExpScale = 0.08838834764831845f * 1.4426950408889634f;
constexpr int kSplit = K_SPLIT;
}

__device__ __forceinline__ void spin_clk(int n) {
  if (n > 0) { const uint32_t t0 = clock(); while ((uint32_t)clock() - t0 < (uint32_t)n) {} }
}

template <bool GATED>
__device__ __forceinline__ void r_project_x(const uint32_t (&w)[112], uint32_t sb, int seg, int warp, int lane, uint32_t rank, int& budget) {
  using namespace rk;
  const int st = seg & 1;
  float d[16];
  mbar_wait(sb + B_XF + 8 * st, (seg >> 1) & 1, budget);
  const uint64_t desc = make_desc(sb + XT + st * 32768, 16, 1024, 1);
  wg_fence();
#pragma unroll
  for (int j = 0; j < kSplit; j++)
    wgmma_rs32<0>(d, w[4 * j], w[4 * j + 1], w[4 * j + 2], w[4 * j + 3], desc + (uint64_t)(((j >> 2) * 4096 + (j & 3) * 32) >> 4), j > 0);
  wg_commit();
  if (GATED) bar_sync(NB_TD, 512);
  wg_fence();
#pragma unroll
  for (int j = kSplit; j < 28; j++)
    wgmma_rs32<0>(d, w[4 * j], w[4 * j + 1], w[4 * j + 2], w[4 * j + 3], desc + (uint64_t)(((j >> 2) * 4096 + (j & 3) * 32) >> 4), j > 0);
  const uint64_t adesc = make_desc(sb + WRES + (warp >> 2) * 8192, 1024, 1024, 1);
#pragma unroll
  for (int j = 0; j < 4; j++) wgmma_ss32<1, 0>(d, adesc + (uint64_t)(j * 128), desc + (uint64_t)((7 * 4096 + j * 32) >> 4), 1);
  wg_commit();
  wg_wait<0>();
  const int slot = seg & 3;
  const uint32_t dst = rank == 0 ? QX + slot * 8192 : KV + slot * 20480 + (rank - 1) * 10240;
  const uint32_t a = sb + dst + (lane >> 4) * 2048 + (16 * warp + (lane & 15)) * 16;
  stsm4(a, pack2(d[0], d[1]), pack2(d[2], d[3]), pack2(d[4], d[5]), pack2(d[6], d[7]));
  stsm4(a + 4096, pack2(d[8], d[9]), pack2(d[10], d[11]), pack2(d[12], d[13]), pack2(d[14], d[15]));
  fence_async_smem();
  bar_sync(NB_P, 256);
  if (warp == 0 && lane == 0) {
    const uint32_t bar = sb + B_KV + 8 * slot;
    if (rank != 0) {
      const uint32_t other = 3 - rank;
      bulk_s2c(mapa(sb + dst, 0), sb + dst, 8192, mapa(bar, 0));
      bulk_s2c(mapa(sb + dst, other), sb + dst, 8192, mapa(bar, other));
    }
    mbar_arrive_tx(bar, rank == 0 ? 16384 : 8192);
  }
}

template <int I>
__device__ __forceinline__ void r_vo_issue(const uint32_t (&wo)[64], float (&d)[16], uint32_t sb, int seg) {
  using namespace rk;
  const uint64_t desc = make_desc(sb + KV + (seg & 3) * 20480 + 10240, 128, 2048, 0);
  const uint64_t adesc = make_desc(sb + WOS, 16, 1024, 1);
  wg_fence();
#pragma unroll
  for (int kk = 0; kk < 8; kk++) {
    if (I < 2) wgmma_rs32<1>(d, wo[32 * I + 4 * kk], wo[32 * I + 4 * kk + 1], wo[32 * I + 4 * kk + 2], wo[32 * I + 4 * kk + 3], desc + (uint64_t)(kk * 16), kk > 0);
    else wgmma_ss32<0, 1>(d, adesc + (uint64_t)(((kk >> 2) * 8192 + (kk & 3) * 32) >> 4), desc + (uint64_t)(kk * 16), kk > 0);
  }
  wg_commit();
}
__device__ __forceinline__ void pack16(uint32_t* o, const float (&d)[16]) {
#pragma unroll
  for (int j = 0; j < 8; j++) o[j] = pack2(d[2 * j], d[2 * j + 1]);
}

template <int NT>
__device__ __forceinline__ void r_attn_role(uint32_t sb, int tw, int lane, uint32_t rank, uint32_t head, const bf16* __restrict__ Wo, int& budget) {
  using namespace rk;
  const int g = lane >> 2, t = lane & 3;
  const int tile0 = (NT == 2 ? 0 : 12 * (int)rank - 4) + tw;
  uint32_t wo[64];
  const uint32_t woa = sb + WOS + (16 * tw + (lane & 15)) * 128;
  const uint32_t wx = (lane >> 4) ^ (lane & 7);
  {
    uint32_t wt[32 * NT];
#pragma unroll
    for (int i = 0; i < NT; i++) {
      const uint32_t* src = reinterpret_cast<const uint32_t*>(Wo + (size_t)(head * 128 + 2 * t) * kD + (tile0 + 4 * i) * 16 + 2 * g);
#pragma unroll
      for (int kk = 0; kk < 8; kk++) {
        wt[32 * i + 4 * kk] = __ldg(src + (16 * kk) * (kD / 2));
        wt[32 * i + 4 * kk + 1] = __ldg(src + (16 * kk + 1) * (kD / 2));
        wt[32 * i + 4 * kk + 2] = __ldg(src + (16 * kk + 8) * (kD / 2));
        wt[32 * i + 4 * kk + 3] = __ldg(src + (16 * kk + 9) * (kD / 2));
      }
    }
#pragma unroll
    for (int j = 0; j < 16 * NT; j++) {
      const uint32_t x = wt[2 * j], y = wt[2 * j + 1];
      wt[2 * j] = __byte_perm(x, y, 0x5410);
      wt[2 * j + 1] = __byte_perm(x, y, 0x7632);
    }
#pragma unroll
    for (int j = 0; j < 64; j++) wo[j] = wt[j];
    if (NT == 3) {
#pragma unroll
      for (int kk = 0; kk < 8; kk++)
        stsm4(woa + (kk >> 2) * 8192 + (((2 * (kk & 3)) ^ wx) << 4), wt[32 * NT - 32 + 4 * kk], wt[32 * NT - 31 + 4 * kk], wt[32 * NT - 30 + 4 * kk], wt[32 * NT - 29 + 4 * kk]);
    } else if (tw == 0) {
      sts128(sb + PS + 5 * 512 + lane * 16, 0u, 0u, 0u, 0u);
    }
    fence_async_smem();
    bar_sync(NB_T, 128);
  }
  unsigned char* mail = g_mail + (size_t)(tile0 * 4 + (lane >> 3)) * 4096 + head * 128 + (lane & 7) * 16;
  uint32_t vox[8 * NT];
  mbar_wait(sb + B_KV, 0, budget);
  {
    float d[16];
    r_vo_issue<0>(wo, d, sb, 0); wg_wait<0>(); pack16(vox, d);
    r_vo_issue<1>(wo, d, sb, 0); wg_wait<0>(); pack16(vox + 8, d);
    if (NT == 3) { r_vo_issue<2>(wo, d, sb, 0); wg_wait<0>(); pack16(vox + 8 * NT - 8, d); }
  }
  for (int s = 0; s < kNSeg; s++) {
    {
      const uint32_t va = sb + KV + (s & 3) * 20480 + 10240 + 8192 + lane * 16;
      float vm[NT][4];
      uint32_t a[8][4], b[16];
      auto lda = [&](int kk) { if (NT == 3) ldsm4(woa + (kk >> 2) * 8192 + (((2 * (kk & 3)) ^ wx) << 4), a[kk][0], a[kk][1], a[kk][2], a[kk][3]); };
      auto ldb = [&](int k2) { ldsm4t(va + k2 * 512, b[4 * k2], b[4 * k2 + 1], b[4 * k2 + 2], b[4 * k2 + 3]); };
      auto round = [&](int kk) {
#pragma unroll
        for (int i = 0; i < NT; i++) {
          const uint32_t* p = i < 2 ? &wo[32 * i + 4 * kk] : a[kk];
          if (kk == 0) mma16z(vm[i], p[0], p[1], p[2], p[3], b[0], b[1]);
          else mma16(vm[i], p[0], p[1], p[2], p[3], b[2 * kk], b[2 * kk + 1]);
        }
      };
      lda(0); lda(1);
      mbar_wait(sb + B_QKV, s & 1, budget);
      ldb(0); ldb(1);
      TMARKD(tw == 0, 3, b[0]);
      round(0); lda(2); round(1); lda(3); ldb(2);
      round(2); lda(4); round(3); lda(5); ldb(3);
      round(4); lda(6);
      bar_sync(NB_S, 256);
      float sv[4][4];
#pragma unroll
      for (int j = 0; j < 4; j++) lds128f(sb + SC + j * 512 + lane * 16, sv[j][0], sv[j][1], sv[j][2], sv[j][3]);
      TMARKD(tw == 0, 4, __float_as_uint(sv[0][0]));
      round(5); lda(7);
      const float u0 = (sv[0][2] + sv[1][2]) + (sv[2][2] + sv[3][2]), u1 = (sv[0][3] + sv[1][3]) + (sv[2][3] + sv[3][3]);
      float m = fmaxf(fmaxf(fmaxf(sv[0][0], sv[0][1]), fmaxf(sv[1][0], sv[1][1])), fmaxf(fmaxf(sv[2][0], sv[2][1]), fmaxf(sv[3][0], sv[3][1])));
      m = fmaxf(m, fmaxf(u0, u1));
      float m2 = __shfl_xor_sync(~0u, m, 1);
      round(6);
      m = fmaxf(m, m2);
      m2 = __shfl_xor_sync(~0u, m, 2);
      round(7);
      const float mb = -fmaxf(m, m2) * kExpScale;
      uint32_t p[5];
#pragma unroll
      for (int j = 0; j < 4; j++) p[j] = pack2(ex2(fmaf(sv[j][0], kExpScale, mb)), ex2(fmaf(sv[j][1], kExpScale, mb)));
      p[4] = pack2(ex2(fmaf(u0, kExpScale, mb)), ex2(fmaf(u1, kExpScale, mb)));
      constexpr uint32_t kOnes = 0x3F803F80u;
      float o[NT][4], sum[4];
      mma16z(sum, kOnes, kOnes, kOnes, kOnes, p[0], p[1]);
#pragma unroll
      for (int i = 0; i < NT; i++) mma16z(o[i], vox[8 * i], vox[8 * i + 1], vox[8 * i + 2], vox[8 * i + 3], p[0], p[1]);
      mma16(sum, kOnes, kOnes, kOnes, kOnes, p[2], p[3]);
#pragma unroll
      for (int i = 0; i < NT; i++) mma16(o[i], vox[8 * i + 4], vox[8 * i + 5], vox[8 * i + 6], vox[8 * i + 7], p[2], p[3]);
      mma8(sum, kOnes, kOnes, p[4]);
#pragma unroll
      for (int i = 0; i < NT; i++) mma8(o[i], pack2(vm[i][0], vm[i][1]), pack2(vm[i][2], vm[i][3]), p[4]);
      const float i0 = rcp(sum[0]), i1 = rcp(sum[1]);
      const uint32_t tag = (s + 1) & 1;
#pragma unroll
      for (int i = 0; i < NT; i++)
        st_b128(mail + i * 16 * 4096, (__float_as_uint(o[i][0] * i0) & ~1u) | tag, __float_as_uint(o[i][2] * i0),
                __float_as_uint(o[i][1] * i1), __float_as_uint(o[i][3] * i1));
      bar_arrive(NB_TD, 512);
      TMARKD(tw == 0, 5, __float_as_uint(o[NT - 1][3] * i1));
      if (tw == 0 && lane == 0) mbar_arrive_tx(sb + B_QKV, 6144);
    }
    if (NT == 3) {
      if (s + 1 < kNSeg) mbar_wait(sb + B_KV + 8 * ((s + 1) & 3), ((s + 1) >> 2) & 1, budget);
      float d0[16], d1[16];
      r_vo_issue<0>(wo, d0, sb, s + 1);
      r_vo_issue<1>(wo, d1, sb, s + 1);
      wg_wait<1>(); pack16(vox, d0);
      r_vo_issue<2>(wo, d0, sb, s + 1);
      wg_wait<1>(); pack16(vox + 8, d1);
      wg_wait<0>(); pack16(vox + 8 * NT - 8, d0);
    } else {
      const uint32_t kb = sb + KV + (s & 3) * 20480;
      float sc[20], d0[16], d1[16];
      {
        const uint64_t qd = make_desc(sb + QX + (s & 3) * 8192, 128, 2048, 0), kd = make_desc(kb, 128, 2048, 0);
        wg_fence();
#pragma unroll
        for (int kk = 0; kk < 8; kk++) wgmma_ss40_tt(sc, qd + (uint64_t)(kk * 16), kd + (uint64_t)(kk * 16), kk > 0);
        wg_commit();
      }
      if (s + 1 < kNSeg) mbar_wait(sb + B_KV + 8 * ((s + 1) & 3), ((s + 1) >> 2) & 1, budget);
      r_vo_issue<0>(wo, d0, sb, s + 1);
      wg_wait<1>();
      {
        const int dl = 16 * tw + g - 2 * t;
        float m0 = fmaxf(sc[16], sc[17]), m1 = fmaxf(sc[18], sc[19]);
#pragma unroll
        for (int n = 0; n < 4; n++) {
          if (8 * n > dl) sc[4 * n] = -INFINITY;
          if (8 * n + 1 > dl) sc[4 * n + 1] = -INFINITY;
          if (8 * n - 8 > dl) sc[4 * n + 2] = -INFINITY;
          if (8 * n - 7 > dl) sc[4 * n + 3] = -INFINITY;
          m0 = fmaxf(m0, fmaxf(sc[4 * n], sc[4 * n + 1]));
          m1 = fmaxf(m1, fmaxf(sc[4 * n + 2], sc[4 * n + 3]));
        }
        m0 = fmaxf(m0, __shfl_xor_sync(~0u, m0, 1)); m1 = fmaxf(m1, __shfl_xor_sync(~0u, m1, 1));
        m0 = fmaxf(m0, __shfl_xor_sync(~0u, m0, 2)); m1 = fmaxf(m1, __shfl_xor_sync(~0u, m1, 2));
        m0 *= -kExpScale; m1 *= -kExpScale;
        float s0 = 0.f, s1 = 0.f;
#pragma unroll
        for (int n = 0; n < 5; n++) {
          sc[4 * n] = ex2(fmaf(sc[4 * n], kExpScale, m0)); sc[4 * n + 1] = ex2(fmaf(sc[4 * n + 1], kExpScale, m0));
          sc[4 * n + 2] = ex2(fmaf(sc[4 * n + 2], kExpScale, m1)); sc[4 * n + 3] = ex2(fmaf(sc[4 * n + 3], kExpScale, m1));
          s0 += sc[4 * n] + sc[4 * n + 1]; s1 += sc[4 * n + 2] + sc[4 * n + 3];
        }
        s0 += __shfl_xor_sync(~0u, s0, 1); s1 += __shfl_xor_sync(~0u, s1, 1);
        s0 += __shfl_xor_sync(~0u, s0, 2); s1 += __shfl_xor_sync(~0u, s1, 2);
        const float i0 = rcp(s0), i1 = rcp(s1);
        uint32_t p[10];
#pragma unroll
        for (int n = 0; n < 5; n++) { p[2 * n] = pack2(sc[4 * n] * i0, sc[4 * n + 1] * i0); p[2 * n + 1] = pack2(sc[4 * n + 2] * i1, sc[4 * n + 3] * i1); }
        if (tw < 2) {
          const uint32_t pa = sb + PS + (lane >> 4) * 512 + (16 * tw + (lane & 15)) * 16;
          stsm4(pa, p[0], p[1], p[2], p[3]);
          stsm4(pa + 1024, p[4], p[5], p[6], p[7]);
          stsm2(pa + 2048, p[8], p[9]);
          fence_async_smem();
        } else if (tw == 2 && lane == 0) {
          asm volatile("cp.async.bulk.wait_group 0;" ::: "memory");
        }
      }
      r_vo_issue<1>(wo, d1, sb, s + 1);
      wg_wait<1>();
      pack16(vox, d0);
      bar_sync(NB_T, 128);
      const uint64_t pd = make_desc(sb + PS, 512, 128, 0);
      const uint64_t vd = make_desc(kb + 10240, 2048, 128, 0), vd2 = make_desc(kb + 10240 + 8192, 0, 128, 0);
      wg_fence();
      wgmma_ss32<0, 0>(d0, vd, pd, 0);
      wgmma_ss32<0, 0>(d0, vd + 256, pd + 64, 1);
      wgmma_ss32<0, 0>(d0, vd2, pd + 128, 1);
      wg_commit();
      wg_wait<1>();
      pack16(vox + 8, d1);
      wg_fence();
      wgmma_ss32<0, 0>(d1, vd + 64, pd, 0);
      wgmma_ss32<0, 0>(d1, vd + 256 + 64, pd + 64, 1);
      wgmma_ss32<0, 0>(d1, vd2 + 64, pd + 128, 1);
      wg_commit();
      const uint32_t oa = sb + OST + ((lane >> 4) * 8 + (lane & 7)) * 128 + (((2 * tw + ((lane >> 3) & 1)) ^ (lane & 7)) << 4);
      wg_wait<1>();
      stsm4t(oa, pack2(d0[0], d0[1]), pack2(d0[2], d0[3]), pack2(d0[4], d0[5]), pack2(d0[6], d0[7]));
      stsm4t(oa + 2048, pack2(d0[8], d0[9]), pack2(d0[10], d0[11]), pack2(d0[12], d0[13]), pack2(d0[14], d0[15]));
      wg_wait<0>();
      stsm4t(oa + 4096, pack2(d1[0], d1[1]), pack2(d1[2], d1[3]), pack2(d1[4], d1[5]), pack2(d1[6], d1[7]));
      stsm4t(oa + 6144, pack2(d1[8], d1[9]), pack2(d1[10], d1[11]), pack2(d1[12], d1[13]), pack2(d1[14], d1[15]));
      fence_async_smem();
      bar_sync(NB_T, 128);
      if (tw == 2 && lane == 0) {
        bf16* dst = g_o + (size_t)((s >> 2) * 64 + head * 2) * 8192 + (s & 3) * 2048;
        bulk_s2g(dst, sb + OST, 4096);
        bulk_s2g(dst + 8192, sb + OST + 4096, 4096);
        asm volatile("cp.async.bulk.commit_group;" ::: "memory");
        if (s) asm volatile("red.release.gpu.global.add.u32 [%0], 1;" ::"l"(&g_cnt[C_O + ((s - 1) >> 2)]) : "memory");
      }
    }
    TMARKD(tw == 0, 6, vox[8 * NT - 1]);
  }
  if (NT == 2 && tw == 2 && lane == 0)
    asm volatile("cp.async.bulk.wait_group 0; red.release.gpu.global.add.u32 [%0], 1;" ::"l"(&g_cnt[C_O + 15]) : "memory");
}

__global__ void __cluster_dims__(3, 1, 1) __launch_bounds__(512, 1)
recur_kernel(const __grid_constant__ CUtensorMap tmX, const __grid_constant__ CUtensorMap tmWq,
             const __grid_constant__ CUtensorMap tmWk, const __grid_constant__ CUtensorMap tmWv,
             const bf16* __restrict__ mem0, const bf16* __restrict__ Wo) {
  using namespace rk;
  extern __shared__ unsigned char smem_raw[];
  const uint32_t sb = (smem_u32(smem_raw) + 1023u) & ~1023u;
  const int warp = threadIdx.x >> 5, lane = threadIdx.x & 31;
  const uint32_t rank = blockIdx.x % 3u, head = blockIdx.x / 3u;
  int budget = 1 << 20;

  if (threadIdx.x == 0) {
    for (int i = 0; i < 4; i++) { mbar_init(sb + B_KV + 8 * i, 1); mbar_init(sb + B_W + 8 * i, 1); }
    mbar_init(sb + B_QKV, 1);
    for (int i = 0; i < 2; i++) mbar_init(sb + B_XF + 8 * i, 1);
    mbar_init(sb + B_FREE, 24);
    asm volatile("fence.mbarrier_init.release.cluster;" ::: "memory");
    mbar_arrive_tx(sb + B_QKV, 6144);
    const CUtensorMap* tw = rank == 0 ? &tmWq : rank == 1 ? &tmWk : &tmWv;
    for (int c = 0; c < 4; c++) {
      mbar_arrive_tx(sb + B_W + 8 * c, 32768);
      for (int i = 0; i < 4; i++) {
        const int kb = 2 * c + (i >> 1), nb = i & 1;
        tma_2d(sb + RA + (kb * 2 + nb) * 8192, tw, head * 128 + nb * 64, kb * 64, sb + B_W + 8 * c);
      }
    }
    for (int st = 0; st < 2; st++) {
      mbar_arrive_tx(sb + B_XF + 8 * st, 32768);
      tma_3d(sb + XT + st * 32768, &tmX, 0, st * 32, 0, sb + B_XF + 8 * st);
    }
  }
  cluster_sync_all();

  if (warp < 8) {
    asm volatile("setmaxnreg.inc.sync.aligned.u32 160;");
    uint32_t w[112];
    const uint32_t wa = sb + RA + (warp >> 2) * 8192 + ((lane >> 4) * 8 + (lane & 7)) * 128 + (((2 * (warp & 3) + ((lane >> 3) & 1)) ^ (lane & 7)) << 4);
#pragma unroll
    for (int c = 0; c < 4; c++) {
      mbar_wait(sb + B_W + 8 * c, 0, budget);
#pragma unroll
      for (int jj = 0; jj < 8; jj++) {
        const int j = 8 * c + jj;
        if (j < 28) ldsm4t(wa + (j >> 2) * 16384 + (j & 3) * 2048, w[4 * j], w[4 * j + 1], w[4 * j + 2], w[4 * j + 3]);
      }
    }
    __syncwarp();
    asm volatile("griddepcontrol.launch_dependents;");
    if (lane < 3) mbar_arrive_remote(mapa(sb + B_FREE, lane));
    mbar_wait_cl(sb + B_FREE, 0, budget);
    r_project_x<false>(w, sb, 0, warp, lane, rank, budget);
    if (threadIdx.x == 0) {
      mbar_arrive_tx(sb + B_XF, 32768);
      tma_3d(sb + XT, &tmX, 0, 64, 0, sb + B_XF);
    }
    r_project_x<false>(w, sb, 1, warp, lane, rank, budget);
    uint32_t ma = sb + MEMS + lane * 16;
    uint32_t dst0 = (rank == 0 ? QM : KV + (rank - 1) * 10240 + 8192) + 256 * warp + 4 * lane;
    OPAQUE(ma); OPAQUE(dst0);
    const uint32_t dstep = rank == 0 ? 0u : 20480u;
    for (int s = 0; s < kNSeg; s++) {
      float c0[4], c1[4];
      uint32_t wx[16], b[16][4];
#pragma unroll
      for (int j = 0; j < 4; j++) ldsm4t(wa + 7 * 16384 + j * 2048, wx[4 * j], wx[4 * j + 1], wx[4 * j + 2], wx[4 * j + 3]);
      const uint32_t dst = dst0 + (s & 3) * dstep;
      auto ldb = [&](int i) { ldsm4(ma + i * 512, b[i][0], b[i][1], b[i][2], b[i][3]); };
      bar_sync(NB_MEM, 384);
      ldb(14); ldb(15); ldb(0);
      TMARKD(warp == 0, 0, b[14][0]);
      mma16z(c0, wx[0], wx[1], wx[2], wx[3], b[14][0], b[14][1]);
      mma16z(c1, wx[4], wx[5], wx[6], wx[7], b[14][2], b[14][3]);
      ldb(1);
      mma16(c0, wx[8], wx[9], wx[10], wx[11], b[15][0], b[15][1]);
      mma16(c1, wx[12], wx[13], wx[14], wx[15], b[15][2], b[15][3]);
      ldb(2); ldb(3);
#pragma unroll
      for (int i = 0; i < 14; i++) {
        mma16(c0, w[8 * i], w[8 * i + 1], w[8 * i + 2], w[8 * i + 3], b[i][0], b[i][1]);
        mma16(c1, w[8 * i + 4], w[8 * i + 5], w[8 * i + 6], w[8 * i + 7], b[i][2], b[i][3]);
        if (i + 4 < 14) ldb(i + 4);
      }
      const uint32_t r0 = pack2(c0[0] + c1[0], c0[1] + c1[1]), r1 = pack2(c0[2] + c1[2], c0[3] + c1[3]);
#pragma unroll
      for (uint32_t d = 0; d < 3; d++) {
        const uint32_t base = mapa(sb, d == 2 ? rank : (rank + 1 + d) % 3u);
        st_async32(base + dst, r0, base + B_QKV);
        st_async32(base + dst + 128, r1, base + B_QKV);
      }
      TMARKD(warp == 0, 1, r1);
      TMARKD(warp == 7, 12, r1);
      bar_sync(NB_P, 256);
      if (s + 2 < kNSeg) r_project_x<true>(w, sb, s + 2, warp, lane, rank, budget);
      else bar_sync(NB_TD, 512);
      TMARKD(warp == 0, 2, 0);
    }
  } else if (warp < 12) {
    asm volatile("setmaxnreg.inc.sync.aligned.u32 136;");
    if (rank == 0) r_attn_role<2>(sb, warp - 8, lane, rank, head, Wo, budget);
    else r_attn_role<3>(sb, warp - 8, lane, rank, head, Wo, budget);
  } else {
    asm volatile("setmaxnreg.dec.sync.aligned.u32 56;");
    const int mw = warp - 12;
    for (int i = threadIdx.x - 384; i < 672; i += 128) st_b128(g_pub + (size_t)(blockIdx.x * 672 + i) * 16, 0u, 0u, 0u, 0u);
    asm volatile("fence.acq_rel.gpu;" ::: "memory");
#pragma unroll
    for (int i = 0; i < 4; i++) {
      const int idx = mw * 128 + i * 32 + lane;
      const uint4 v = __ldg(reinterpret_cast<const uint4*>(mem0 + (idx & 7) * kD + (idx >> 3) * 8));
      sts128(sb + MEMS + idx * 16, v.x, v.y, v.z, v.w);
    }
    const int unit = mw == 0 ? (int)blockIdx.x : (mw == 1 && rank == 1) ? 96 + (int)head : -1;
    const uint32_t mo = unit * 4096 + lane * 16;
    const uint32_t pw = ((lane >> 3) & 1) * 8192 + (unit >> 1) * 128 + (2 * (lane & 3) + (lane >> 4)) * 16 + (unit & 1) * 8 + ((lane >> 2) & 1) * 4;
    const uint32_t po = (head & 1) * 8192 + mw * 2048 + lane * 16;
    for (int s = 0;; s++) {
      if (mw < 3) bar_arrive(NB_MEM, 384);
      else {
        bar_sync(NB_MEM, 384);
        if (s + 3 < kNSeg && lane == 0) {
          const uint32_t st = (s + 1) & 1;
          mbar_arrive_tx(sb + B_XF + 8 * st, 32768);
          tma_3d(sb + XT + st * 32768, &tmX, 0, (s + 3) * 32, 0, sb + B_XF + 8 * st);
        }
        __syncwarp();
      }
      {
        mbar_wait(sb + B_KV + 8 * (s & 3), (s >> 2) & 1, budget);
        uint32_t rot = mw * 512, ln = lane;
        asm volatile("" : "+r"(rot), "+r"(ln));
        const uint32_t ka = sb + KV + (s & 3) * 20480 + ln * 16;
        const uint32_t qa = sb + QM + (((ln >> 3) & 1) * 2 + (ln >> 4)) * 128 + (ln & 7) * 16;
        uint32_t kf[16], q[16], km[4], qad[4], kma = ka + 8192 + rot;
#pragma unroll
        for (int i = 0; i < 4; i++) ldsm4t(ka + rot * 4 + (rot ^ (i * 512)), kf[4 * i], kf[4 * i + 1], kf[4 * i + 2], kf[4 * i + 3]);
#pragma unroll
        for (int i = 0; i < 4; i++) qad[i] = qa + (rot ^ (i * 512));
        asm volatile("" : "+r"(qad[0]), "+r"(qad[1]), "+r"(qad[2]), "+r"(qad[3]), "+r"(kma));
        mbar_wait(sb + B_QKV, s & 1, budget);
#pragma unroll
        for (int i = 0; i < 4; i++) ldsm4t(qad[i], q[4 * i], q[4 * i + 1], q[4 * i + 2], q[4 * i + 3]);
        ldsm4t(kma, km[0], km[1], km[2], km[3]);
        float c0[4], c1[4], cm0[4], cm1[4];
        mma16z(c0, q[0], q[1], q[2], q[3], kf[0], kf[1]);
        mma16z(c1, q[0], q[1], q[2], q[3], kf[2], kf[3]);
        mma16(c0, q[4], q[5], q[6], q[7], kf[4], kf[5]);
        mma16(c1, q[4], q[5], q[6], q[7], kf[6], kf[7]);
        mma16z(cm0, q[0], q[1], q[2], q[3], km[0], km[1]);
        mma16(c0, q[8], q[9], q[10], q[11], kf[8], kf[9]);
        mma16(c1, q[8], q[9], q[10], q[11], kf[10], kf[11]);
        mma16z(cm1, q[0], q[1], q[2], q[3], km[2], km[3]);
        mma16(c0, q[12], q[13], q[14], q[15], kf[12], kf[13]);
        mma16(c1, q[12], q[13], q[14], q[15], kf[14], kf[15]);
        sts128(sb + SC + mw * 512 + lane * 16, __float_as_uint(c0[0] + c1[2]), __float_as_uint(c0[1] + c1[3]),
               __float_as_uint(cm0[0] + cm1[2]), __float_as_uint(cm0[1] + cm1[3]));
        bar_arrive(NB_S, 256);
        TMARKD(mw == 0, 13, __float_as_uint(c1[3]));
      }
      bar_sync(NB_TD, 512);
      if (s + 1 == kNSeg) break;
      if (unit >= 0) {
        spin_clk(RED_DELAY);
        const uint32_t tag = (s + 1) & 1;
        const unsigned char* mb = g_mail + mo;
        uint32_t x[8][4];
#pragma unroll
        for (int i = 0; i < 8; i++) ld_b128(mb + i * 512, x[i][0], x[i][1], x[i][2], x[i][3]);
        while (true) {
          uint32_t bad = 0;
#pragma unroll
          for (int i = 0; i < 8; i++) bad |= x[i][0] ^ tag;
          if (!__any_sync(~0u, bad & 1u)) break;
          if (--budget < 0) break;
#pragma unroll
          for (int i = 0; i < 8; i++)
            if ((x[i][0] ^ tag) & 1u) ld_b128(mb + i * 512, x[i][0], x[i][1], x[i][2], x[i][3]);
        }
        TMARKD(mw == 0, 8, x[7][0]);
        float v[4];
#pragma unroll
        for (int j = 0; j < 4; j++)
          v[j] = ((__uint_as_float(x[0][j]) + __uint_as_float(x[1][j])) + (__uint_as_float(x[2][j]) + __uint_as_float(x[3][j]))) +
                 ((__uint_as_float(x[4][j]) + __uint_as_float(x[5][j])) + (__uint_as_float(x[6][j]) + __uint_as_float(x[7][j])));
        const bool hi = lane & 16;
        float k0 = hi ? v[2] : v[0], k1 = hi ? v[3] : v[1];
        k0 += __shfl_xor_sync(~0u, hi ? v[0] : v[2], 16);
        k1 += __shfl_xor_sync(~0u, hi ? v[1] : v[3], 16);
        k0 += __shfl_xor_sync(~0u, k0, 8);
        k1 += __shfl_xor_sync(~0u, k1, 8);
        uint32_t wv = pack2(k0, k1);
        if (wv == 0u) wv = 0x80000000u;
        st_u32(g_pub + (pw + (uint32_t)s * 16384u), wv);
        TMARKD(mw == 0, 9, wv);
      }
      bar_sync(NB_PUB, 128);
      {
        spin_clk(POLL_DELAY);
        const unsigned char* pp = g_pub + (po + (uint32_t)s * 16384u);
        uint32_t x[4][4];
#pragma unroll
        for (int i = 0; i < 4; i++) ld_v4(pp + i * 512, x[i][0], x[i][1], x[i][2], x[i][3]);
        while (true) {
          bool ok = true;
#pragma unroll
          for (int i = 0; i < 4; i++) {
            sts128(sb + MEMS + mw * 2048 + i * 512 + lane * 16, x[i][0], x[i][1], x[i][2], x[i][3]);
            ok = ok && x[i][0] != 0u && x[i][1] != 0u && x[i][2] != 0u && x[i][3] != 0u;
          }
          if (__all_sync(~0u, ok)) break;
          if (--budget < 0) break;
#pragma unroll
          for (int i = 0; i < 4; i++)
            if (x[i][0] == 0u || x[i][1] == 0u || x[i][2] == 0u || x[i][3] == 0u) ld_v4(pp + i * 512, x[i][0], x[i][1], x[i][2], x[i][3]);
        }
        TMARKD(mw == 0, 10, x[3][0]);
        TMARKD(mw == 3, 11, x[3][0]);
      }
    }
  }
  cluster_sync_all();
}

namespace gk {
constexpr int kCtas = 36, kStages = 4;
constexpr uint32_t STG = 49152;
constexpr uint32_t EPI = kStages * STG;
constexpr uint32_t BAR = EPI + 32768;
constexpr uint32_t INFO = BAR + 64;
constexpr uint32_t AUX = INFO + 16;
constexpr uint32_t SMEM = AUX + 64 + 1024;
constexpr int kF1 = 224, kF2 = 32;
constexpr int kFirstSplit = 9;
__host__ __device__ constexpr int nsplit(int rb) { return rb < 9 ? 1 : rb < 12 ? 2 : rb < 14 ? 4 : rb == 14 ? 8 : 16; }
constexpr int kWo = 2 * (9 + 6 + 8 + 8 + 16);
constexpr int kUnits = kF1 + kF2 + kWo;
constexpr uint32_t kDraws = kUnits + kCtas;
constexpr int NB_EPI = 1, NB_DEP = 2;
}

__device__ __forceinline__ void wgmma_256(float (&d)[128], uint64_t adesc, uint64_t bdesc, int acc) {
  asm volatile("{.reg .pred p; setp.ne.b32 p, %130, 0;\n"
    "wgmma.mma_async.sync.aligned.m64n256k16.f32.bf16.bf16 {"
    "%0,%1,%2,%3,%4,%5,%6,%7,%8,%9,%10,%11,%12,%13,%14,%15,%16,%17,%18,%19,%20,%21,%22,%23,%24,%25,%26,%27,%28,%29,%30,%31,"
    "%32,%33,%34,%35,%36,%37,%38,%39,%40,%41,%42,%43,%44,%45,%46,%47,%48,%49,%50,%51,%52,%53,%54,%55,%56,%57,%58,%59,%60,%61,%62,%63,"
    "%64,%65,%66,%67,%68,%69,%70,%71,%72,%73,%74,%75,%76,%77,%78,%79,%80,%81,%82,%83,%84,%85,%86,%87,%88,%89,%90,%91,%92,%93,%94,%95,"
    "%96,%97,%98,%99,%100,%101,%102,%103,%104,%105,%106,%107,%108,%109,%110,%111,%112,%113,%114,%115,%116,%117,%118,%119,%120,%121,%122,%123,%124,%125,%126,%127"
    "}, %128, %129, p, 1, 1, 0, 1;}"
#define D8(i) "+f"(d[i]), "+f"(d[i + 1]), "+f"(d[i + 2]), "+f"(d[i + 3]), "+f"(d[i + 4]), "+f"(d[i + 5]), "+f"(d[i + 6]), "+f"(d[i + 7])
    : D8(0), D8(8), D8(16), D8(24), D8(32), D8(40), D8(48), D8(56), D8(64), D8(72), D8(80), D8(88), D8(96), D8(104), D8(112), D8(120)
#undef D8
    : "l"(adesc), "l"(bdesc), "r"(acc));
}
__device__ __forceinline__ void bulk_g2s(uint32_t dst, const void* src, uint32_t bytes, uint32_t bar) {
  asm volatile("cp.async.bulk.shared::cluster.global.mbarrier::complete_tx::bytes [%0], [%1], %2, [%3];" ::"r"(dst), "l"(src), "r"(bytes), "r"(bar) : "memory");
}
__device__ __forceinline__ uint32_t ld_acq(const unsigned* p) { uint32_t v; asm volatile("ld.acquire.gpu.global.u32 %0, [%1];" : "=r"(v) : "l"(p) : "memory"); return v; }
__device__ __forceinline__ void wait_count(const unsigned* p, uint32_t target, int& budget) {
  while ((int)(ld_acq(p) - target) < 0) { spend(budget); __nanosleep(64); }
}
__device__ __forceinline__ float sigmoidf_(float x) { float t; asm("tanh.approx.f32 %0, %1;" : "=f"(t) : "f"(0.5f * x)); return fmaf(t, 0.5f, 0.5f); }
__device__ __forceinline__ void lds128(uint32_t a, uint32_t& x, uint32_t& y, uint32_t& z, uint32_t& w) {
  asm volatile("ld.shared.v4.u32 {%0,%1,%2,%3}, [%4];" : "=r"(x), "=r"(y), "=r"(z), "=r"(w) : "r"(a) : "memory");
}
__device__ __forceinline__ uint32_t add_bf2(uint32_t a, uint32_t b) { uint32_t r; asm("add.rn.bf16x2 %0, %1, %2;" : "=r"(r) : "r"(a), "r"(b)); return r; }

template <bool ADD>
__device__ __forceinline__ void g_store_out(const float (&d)[128], float s0, float s1, uint32_t stg, bf16* __restrict__ dst, int lane) {
  const uint32_t wa = stg + (lane & 15) * 256, wx = (lane >> 4) ^ (lane & 7);
#pragma unroll
  for (int h = 0; h < 2; h++) {
    uint4 prev[8];
    if (ADD) {
#pragma unroll
      for (int i = 0; i < 8; i++) prev[i] = __ldcg(reinterpret_cast<const uint4*>(dst + (2 * i + (lane >> 4)) * kD + h * 128 + (lane & 15) * 8));
    }
#pragma unroll
    for (int i = 0; i < 8; i++) {
      const float* p = d + 64 * h + 8 * i;
      stsm4(wa + (((2 * i) ^ wx) << 4), pack2(p[0] * s0, p[1] * s0), pack2(p[2] * s1, p[3] * s1), pack2(p[4] * s0, p[5] * s0), pack2(p[6] * s1, p[7] * s1));
    }
    __syncwarp();
#pragma unroll
    for (int i = 0; i < 8; i++) {
      const int row = 2 * i + (lane >> 4);
      uint4 v;
      lds128(stg + row * 256 + (((lane & 15) ^ (row & 7)) << 4), v.x, v.y, v.z, v.w);
      if (ADD) { v.x = add_bf2(v.x, prev[i].x); v.y = add_bf2(v.y, prev[i].y); v.z = add_bf2(v.z, prev[i].z); v.w = add_bf2(v.w, prev[i].w); }
      *reinterpret_cast<uint4*>(dst + row * kD + h * 128 + (lane & 15) * 8) = v;
    }
    __syncwarp();
  }
}

__global__ void __launch_bounds__(384, 1)
gemm_kernel(const __grid_constant__ CUtensorMap tmX, const __grid_constant__ CUtensorMap tmWg, const __grid_constant__ CUtensorMap tmWu,
            const __grid_constant__ CUtensorMap tmWd, const __grid_constant__ CUtensorMap tmWo,
            const bf16* __restrict__ x, const bf16* __restrict__ gw, bf16* __restrict__ out) {
  using namespace gk;
  extern __shared__ unsigned char smem_raw[];
  const uint32_t sb = (smem_u32(smem_raw) + 1023u) & ~1023u;
  const int warp = __shfl_sync(~0u, threadIdx.x >> 5, 0), lane = threadIdx.x & 31;
  int budget = 1 << 20;
  if (threadIdx.x == 0) {
    for (int i = 0; i < kStages; i++) { mbar_init(sb + BAR + 8 * i, 1); mbar_init(sb + BAR + 32 + 8 * i, 2); }
    asm volatile("fence.mbarrier_init.release.cluster;" ::: "memory");
  }
  __syncthreads();

  if (warp < 4) {
    asm volatile("setmaxnreg.dec.sync.aligned.u32 40;");
    if (warp == 0) {
      if (lane == 0) {
        uint32_t it = 0;
        while (true) {
          const uint32_t tk = atomicAdd(&g_ticket, 1u);
          const uint32_t ep = tk / kDraws + 1;
          int u = tk % kDraws, type, rb, nb, piece = 0, k0 = 0, nk;
          if (u < kF1) { type = 0; rb = u / 14; nb = u % 14; nk = 8; }
          else if (u < kF1 + kF2) { type = 1; rb = (u - kF1) >> 1; nb = u & 1; nk = 28; }
          else if (u < kUnits) {
            type = 2; u -= kF1 + kF2; rb = 0;
            while (u >= 2 * nsplit(rb)) { u -= 2 * nsplit(rb); rb++; }
            nb = u & 1; piece = u >> 1; nk = 64 / nsplit(rb); k0 = piece * nk;
          } else { type = 3; rb = nb = 0; nk = 1; }
          const uint32_t code = type | rb << 2 | nb << 6 | piece << 10 | ep << 14;
          const bf16* asrc = type == 1 ? g_hid + (size_t)rb * 28 * 8192 : g_o + (size_t)(rb * 64 + k0) * 8192;
          const int pre = type == 0 ? 0 : nk < kStages ? nk : kStages;
          for (int k = 0; k < nk; k++) {
            const uint32_t st = (it + k) % kStages, ph = ((it + k) / kStages) & 1;
            const uint32_t full = sb + BAR + 8 * st, sa = sb + st * STG;
            mbar_wait(full + 32, ph ^ 1, budget);
            asm volatile("st.shared.u32 [%0], %1;" ::"r"(sb + INFO + 4 * st), "r"(code) : "memory");
            if (type == 3) { mbar_arrive(full); break; }
            mbar_arrive_tx(full, STG);
            if (type == 0) {
              tma_2d(sa, &tmX, k * 64, rb * 128, full);
              tma_3d(sa + 16384, &tmWg, 0, k * 64, nb * 2, full);
              tma_3d(sa + 32768, &tmWu, 0, k * 64, nb * 2, full);
            } else {
              tma_3d(sa + 16384, type == 1 ? &tmWd : &tmWo, 0, (k0 + k) * 64, nb * 4, full);
              if (k >= pre) bulk_g2s(sa, asrc + k * 8192, 16384, full);
              else if (k == pre - 1) {
                if (type == 1) wait_count(&g_cnt[C_HID + rb], ep * 16, budget);
                else wait_count(&g_cnt[C_O + rb], ep * 128, budget);
                asm volatile("fence.proxy.async.global;" ::: "memory");
                for (int j = 0; j < pre; j++) bulk_g2s(sb + ((it + j) % kStages) * STG, asrc + j * 8192, 16384, sb + BAR + 8 * ((it + j) % kStages));
              }
            }
          }
          if (type == 3) break;
          it += nk;
        }
      }
    } else if (warp == 1) {
      while (true) {
        bar_sync(NB_EPI, 288);
        uint32_t idx;
        asm volatile("ld.shared.u32 %0, [%1];" : "=r"(idx) : "r"(sb + AUX) : "memory");
        bar_arrive(NB_DEP, 288);
        if (idx == ~0u) break;
        if (lane == 0) asm volatile("fence.proxy.async.global; red.release.gpu.global.add.u32 [%0], 1;" ::"l"(&g_cnt[idx]) : "memory");
      }
    } else if (blockIdx.x < 16) {
      float w[16];
#pragma unroll
      for (int i = 0; i < 2; i++) {
        const uint4 v = __ldg(reinterpret_cast<const uint4*>(gw + i * 256 + lane * 8));
        const uint32_t q[4] = {v.x, v.y, v.z, v.w};
#pragma unroll
        for (int j = 0; j < 4; j++) { w[8 * i + 2 * j] = __uint_as_float(q[j] << 16); w[8 * i + 2 * j + 1] = __uint_as_float(q[j] & 0xffff0000u); }
      }
      const int r0 = blockIdx.x * 128 + (warp - 2) * 64;
      for (int r = r0; r < r0 + 64; r++) {
        float a = 0.f;
#pragma unroll
        for (int i = 0; i < 2; i++) {
          const uint4 v = __ldg(reinterpret_cast<const uint4*>(x + r * kD + i * 256 + lane * 8));
          const uint32_t q[4] = {v.x, v.y, v.z, v.w};
#pragma unroll
          for (int j = 0; j < 4; j++) a = fmaf(__uint_as_float(q[j] << 16), w[8 * i + 2 * j], fmaf(__uint_as_float(q[j] & 0xffff0000u), w[8 * i + 2 * j + 1], a));
        }
#pragma unroll
        for (int o = 16; o; o >>= 1) a += __shfl_xor_sync(~0u, a, o);
        if (lane == 0) g_gate[r] = 1.f / (1.f + __expf(-a));
      }
      if (lane == 0) asm volatile("red.release.gpu.global.add.u32 [%0], 1;" ::"l"(&g_cnt[C_HID + blockIdx.x]) : "memory");
    }
  } else {
    asm volatile("setmaxnreg.inc.sync.aligned.u32 232;");
    const int cw = warp - 4, ct = threadIdx.x - 128;
    const uint32_t stg = sb + EPI + cw * 4096;
    uint32_t it = 0;
    bool pending = false;
    float d[128];
    while (true) {
      mbar_wait(sb + BAR + 8 * (it % kStages), (it / kStages) & 1, budget);
      uint32_t code;
      asm volatile("ld.shared.u32 %0, [%1];" : "=r"(code) : "r"(sb + INFO + 4 * (it % kStages)) : "memory");
      const int type = code & 3, rb = (code >> 2) & 15, nb = (code >> 6) & 15;
      const uint32_t ep = code >> 14;
      if (type == 3) break;
      const int nk = type == 0 ? 8 : type == 1 ? 28 : 64 / nsplit(rb);
      for (int k = 0; k < nk; k++, it++) {
        const uint32_t st = it % kStages;
        if (k) mbar_wait(sb + BAR + 8 * st, (it / kStages) & 1, budget);
        const uint64_t ad = make_desc(sb + st * STG + (cw >> 2) * 8192, 16, 1024, 1);
        const uint64_t bd = make_desc(sb + st * STG + 16384, 8192, 1024, 1);
        wg_fence();
#pragma unroll
        for (int j = 0; j < 4; j++) wgmma_256(d, ad + (uint64_t)(2 * j), bd + (uint64_t)(128 * j), k | j);
        wg_commit();
        wg_wait<1>();
        if (k && (ct & 127) == 0) mbar_arrive(sb + BAR + 32 + 8 * ((it - 1) % kStages));
      }
      wg_wait<0>();
      if ((ct & 127) == 0) mbar_arrive(sb + BAR + 32 + 8 * ((it - 1) % kStages));
      const int row = rb * 128 + cw * 16;
      uint32_t flag = ~1u;
      if (type == 0) {
        const uint32_t wa = stg + (lane & 15) * 128, wx = (lane >> 4) ^ (lane & 7);
#pragma unroll
        for (int i = 0; i < 8; i++) {
          float h[8];
#pragma unroll
          for (int j = 0; j < 8; j++) h[j] = sigmoidf_(d[8 * i + j]) * d[64 + 8 * i + j];
          stsm4(wa + (i >> 2) * 2048 + (((2 * (i & 3)) ^ wx) << 4), pack2(h[0], h[1]), pack2(h[2], h[3]), pack2(h[4], h[5]), pack2(h[6], h[7]));
        }
        __syncwarp();
        bf16* dst = g_hid + (size_t)(rb * 28 + nb * 2) * 8192 + cw * 1024 + lane * 8;
#pragma unroll
        for (int i = 0; i < 8; i++) {
          uint4 v;
          lds128(stg + i * 512 + lane * 16, v.x, v.y, v.z, v.w);
          *reinterpret_cast<uint4*>(dst + (i >> 2) * 8192 + (i & 3) * 256) = v;
        }
        __syncwarp();
        flag = C_HID + rb;
      } else {
        const int tile = rb * 2 + nb;
        float4* acc = reinterpret_cast<float4*>(g_acc) + (size_t)(tile - 2 * kFirstSplit) * 8192 + ct;
        bf16* dst = out + row * kD + nb * 256;
        if (type == 2) {
          if (lane == 0) wait_count(&g_cnt[C_F2 + tile], ep, budget);
          __syncwarp();
        }
        const float g0 = __ldcg(&g_gate[row + (lane >> 2)]), g1 = __ldcg(&g_gate[row + 8 + (lane >> 2)]);
        if (type == 1) {
          const float s0 = 1.f - g0, s1 = 1.f - g1;
          if (rb < kFirstSplit) g_store_out<false>(d, s0, s1, stg, dst, lane);
          else {
#pragma unroll
            for (int i = 0; i < 32; i++) acc[i * 256] = make_float4(d[4 * i] * s0, d[4 * i + 1] * s0, d[4 * i + 2] * s1, d[4 * i + 3] * s1);
          }
          flag = C_F2 + tile;
        } else if (rb < kFirstSplit) {
          g_store_out<true>(d, g0, g1, stg, dst, lane);
        } else {
          const uint32_t ns = nsplit(rb);
          uint32_t tk = 0;
          if (lane == 0) tk = atomicAdd(&g_cnt[C_ARR + tile * 8 + cw], 1u);
          tk = __shfl_sync(~0u, tk, 0);
          if (tk != ep * ns - 1) {
#pragma unroll
            for (int i = 0; i < 32; i++)
              asm volatile("red.relaxed.gpu.global.add.v4.f32 [%0], {%1,%2,%3,%4};" ::"l"(acc + i * 256), "f"(d[4 * i] * g0), "f"(d[4 * i + 1] * g0),
                           "f"(d[4 * i + 2] * g1), "f"(d[4 * i + 3] * g1) : "memory");
            __syncwarp();
            if (lane == 0) asm volatile("red.release.gpu.global.add.u32 [%0], 1;" ::"l"(&g_cnt[C_DONE + tile * 8 + cw]) : "memory");
          } else {
            if (lane == 0) wait_count(&g_cnt[C_DONE + tile * 8 + cw], ep * (ns - 1), budget);
            __syncwarp();
#pragma unroll
            for (int i = 0; i < 32; i++) {
              const float4 v = __ldcg(acc + i * 256);
              d[4 * i] = fmaf(d[4 * i], g0, v.x); d[4 * i + 1] = fmaf(d[4 * i + 1], g0, v.y);
              d[4 * i + 2] = fmaf(d[4 * i + 2], g1, v.z); d[4 * i + 3] = fmaf(d[4 * i + 3], g1, v.w);
            }
            g_store_out<false>(d, 1.f, 1.f, stg, dst, lane);
          }
        }
      }
      if (flag != ~1u) {
        if (pending) bar_sync(NB_DEP, 288);
        if (ct == 0) asm volatile("st.shared.u32 [%0], %1;" ::"r"(sb + AUX), "r"(flag) : "memory");
        bar_arrive(NB_EPI, 288);
        pending = true;
      }
    }
    if (pending) bar_sync(NB_DEP, 288);
    if (ct == 0) asm volatile("st.shared.u32 [%0], %1;" ::"r"(sb + AUX), "r"(~0u) : "memory");
    bar_arrive(NB_EPI, 288);
    bar_sync(NB_DEP, 288);
  }
}

typedef CUresult (*EncodeFn)(CUtensorMap*, CUtensorMapDataType, cuuint32_t, void*, const cuuint64_t*, const cuuint64_t*,
                             const cuuint32_t*, const cuuint32_t*, CUtensorMapInterleave, CUtensorMapSwizzle,
                             CUtensorMapL2promotion, CUtensorMapFloatOOBfill);

static void make_map(EncodeFn fn, CUtensorMap* m, const void* base, uint64_t cols, uint64_t rows, uint32_t bc, uint32_t br) {
  cuuint64_t dims[2] = {cols, rows};
  cuuint64_t strides[1] = {cols * 2};
  cuuint32_t box[2] = {bc, br};
  cuuint32_t es[2] = {1, 1};
  fn(m, CU_TENSOR_MAP_DATA_TYPE_BFLOAT16, 2, const_cast<void*>(base), dims, strides, box, es, CU_TENSOR_MAP_INTERLEAVE_NONE,
     CU_TENSOR_MAP_SWIZZLE_128B, CU_TENSOR_MAP_L2_PROMOTION_L2_256B, CU_TENSOR_MAP_FLOAT_OOB_FILL_NONE);
}

static void make_map3(EncodeFn fn, CUtensorMap* m, const void* base, uint64_t cols, uint64_t rows, uint32_t br, uint32_t nc) {
  cuuint64_t dims[3] = {64, rows, cols / 64};
  cuuint64_t strides[2] = {cols * 2, 128};
  cuuint32_t box[3] = {64, br, nc};
  cuuint32_t es[3] = {1, 1, 1};
  fn(m, CU_TENSOR_MAP_DATA_TYPE_BFLOAT16, 3, const_cast<void*>(base), dims, strides, box, es, CU_TENSOR_MAP_INTERLEAVE_NONE,
     CU_TENSOR_MAP_SWIZZLE_128B, CU_TENSOR_MAP_L2_PROMOTION_L2_256B, CU_TENSOR_MAP_FLOAT_OOB_FILL_NONE);
}

extern "C" void kernel_launch(void* const* d_in, const int* in_sizes, int n_in, void* d_out, int out_size) {
  const bf16* x = (const bf16*)d_in[0];
  const bf16* mem0 = (const bf16*)d_in[1];
  const bf16* Wo = (const bf16*)d_in[5];
  void* fp = nullptr;
  cudaDriverEntryPointQueryResult qr;
  cudaGetDriverEntryPoint("cuTensorMapEncodeTiled", &fp, cudaEnableDefault, &qr);
  EncodeFn fn = (EncodeFn)fp;
  CUtensorMap tmX, tmWq, tmWk, tmWv;
  make_map3(fn, &tmX, x, kD, kS, 32, 8);
  make_map(fn, &tmWq, d_in[2], 4096, kD, 64, 64);
  make_map(fn, &tmWk, d_in[3], 4096, kD, 64, 64);
  make_map(fn, &tmWv, d_in[4], 4096, kD, 64, 64);
  cudaFuncSetAttribute(recur_kernel, cudaFuncAttributeMaxDynamicSharedMemorySize, rk::SMEM);
  recur_kernel<<<96, 512, rk::SMEM>>>(tmX, tmWq, tmWk, tmWv, mem0, Wo);
  CUtensorMap tmX2, tmWg, tmWu, tmWd, tmWo;
  make_map(fn, &tmX2, x, kD, kS, 64, 128);
  make_map3(fn, &tmWg, d_in[8], kF, kD, 64, 2);
  make_map3(fn, &tmWu, d_in[9], kF, kD, 64, 2);
  make_map3(fn, &tmWd, d_in[10], kD, kF, 64, 4);
  make_map3(fn, &tmWo, Wo, kD, 4096, 64, 4);
  cudaFuncSetAttribute(gemm_kernel, cudaFuncAttributeMaxDynamicSharedMemorySize, gk::SMEM);
  cudaLaunchConfig_t cfg = {};
  cfg.gridDim = dim3(gk::kCtas);
  cfg.blockDim = dim3(384);
  cfg.dynamicSmemBytes = gk::SMEM;
  cfg.stream = cudaStreamPerThread;
  cudaLaunchAttribute at[1];
  at[0].id = cudaLaunchAttributeProgrammaticStreamSerialization;
  at[0].val.programmaticStreamSerializationAllowed = 1;
  cfg.attrs = at;
  cfg.numAttrs = 1;
  cudaLaunchKernelEx(&cfg, gemm_kernel, tmX2, tmWg, tmWu, tmWd, tmWo, x, (const bf16*)d_in[11], (bf16*)d_out);
}
```

```cpp
#include <cuda_runtime.h>
#include <cuda_bf16.h>
#include <cuda.h>
#include <stdint.h>

typedef __nv_bfloat16 bf16;

constexpr int kS = 2048, kD = 512, kH = 32, kF = 1792, kNSeg = 64;

__device__ __align__(8192) unsigned char g_mail[128 * 8192];
__device__ __align__(8192) unsigned char g_pub[65536];
__device__ __align__(16) unsigned g_tab[128];
__device__ __align__(128) unsigned g_anc[96];
__device__ __align__(1024) bf16 g_o[(size_t)kS * 4096];
__device__ __align__(1024) bf16 g_hid[kS * kF];
__device__ __align__(16) float g_acc[14 * 128 * 256];
__device__ float g_gate[kS];
__device__ unsigned g_ticket;
constexpr int C_HID = 0, C_O = 16, C_F2 = 32, C_ARR = 64, C_DONE = 320;
__device__ unsigned g_cnt[576];

#define TMARKD(cond, ev, dep)
#define TMARKV(cond, ev, v)
#define OPAQUE(v_) v_ = __shfl_xor_sync(~0u, v_, 0)

__device__ __forceinline__ uint32_t smem_u32(const void* p) { return (uint32_t)__cvta_generic_to_shared(p); }
__device__ __forceinline__ void mbar_init(uint32_t a, uint32_t n) { asm volatile("mbarrier.init.shared::cta.b64 [%0], %1;" ::"r"(a), "r"(n) : "memory"); }
__device__ __forceinline__ void mbar_arrive(uint32_t a) { asm volatile("mbarrier.arrive.shared::cta.b64 _, [%0];" ::"r"(a) : "memory"); }
__device__ __forceinline__ void mbar_arrive_tx(uint32_t a, uint32_t b) { asm volatile("mbarrier.arrive.expect_tx.shared::cta.b64 _, [%0], %1;" ::"r"(a), "r"(b) : "memory"); }
__device__ __forceinline__ void mbar_arrive_remote(uint32_t a) { asm volatile("mbarrier.arrive.release.cluster.shared::cluster.b64 _, [%0];" ::"r"(a) : "memory"); }
__device__ __forceinline__ bool mbar_try(uint32_t a, uint32_t par) {
  uint32_t ok;
  asm volatile("{.reg .pred p; mbarrier.try_wait.parity.shared::cta.b64 p, [%1], %2; selp.u32 %0, 1, 0, p;}" : "=r"(ok) : "r"(a), "r"(par) : "memory");
  return ok;
}
__device__ __forceinline__ bool mbar_try_cl(uint32_t a, uint32_t par) {
  uint32_t ok;
  asm volatile("{.reg .pred p; mbarrier.try_wait.parity.acquire.cluster.shared::cta.b64 p, [%1], %2; selp.u32 %0, 1, 0, p;}" : "=r"(ok) : "r"(a), "r"(par) : "memory");
  return ok;
}
__device__ __forceinline__ void spend(int& budget) { asm volatile("{.reg .pred p; .reg .u64 z; mov.u64 z, 0; add.s32 %0, %0, -1; setp.lt.s32 p, %0, 0; @p st.global.u32 [z], %0;}" : "+r"(budget)); }
__device__ __forceinline__ void mbar_wait(uint32_t a, uint32_t par, int& budget) { while (!mbar_try(a, par)) { spend(budget); } }
__device__ __forceinline__ void mbar_wait_cl(uint32_t a, uint32_t par, int& budget) { while (!mbar_try_cl(a, par)) { spend(budget); } }
__device__ __forceinline__ uint32_t mapa(uint32_t a, uint32_t r) { uint32_t o; asm("mapa.shared::cluster.u32 %0, %1, %2;" : "=r"(o) : "r"(a), "r"(r)); return o; }
__device__ __forceinline__ void fence_async_smem() { asm volatile("fence.proxy.async.shared::cta;" ::: "memory"); }
__device__ __forceinline__ void bar_sync(int id, int n) { asm volatile("bar.sync %0, %1;" ::"r"(id), "r"(n) : "memory"); }
__device__ __forceinline__ void bar_sync_after(int id, int n, uint32_t dep) {
  asm volatile("{.reg .pred p; setp.eq.u32 p, %2, 0; @p bar.sync %0, %1;}" ::"r"(id), "r"(n), "r"(dep & blockIdx.y) : "memory");
}
__device__ __forceinline__ void bar_arrive(int id, int n) { asm volatile("bar.arrive %0, %1;" ::"r"(id), "r"(n) : "memory"); }
__device__ __forceinline__ void cluster_sync_all() {
  asm volatile("barrier.cluster.arrive.release.aligned; barrier.cluster.wait.acquire.aligned;" ::: "memory");
}
__device__ __forceinline__ void tma_2d(uint32_t dst, const CUtensorMap* tm, int c0, int c1, uint32_t bar) {
  asm volatile("cp.async.bulk.tensor.2d.shared::cluster.global.mbarrier::complete_tx::bytes [%0], [%1, {%3, %4}], [%2];"
               ::"r"(dst), "l"(tm), "r"(bar), "r"(c0), "r"(c1) : "memory");
}
__device__ __forceinline__ void tma_3d(uint32_t dst, const CUtensorMap* tm, int c0, int c1, int c2, uint32_t bar) {
  asm volatile("cp.async.bulk.tensor.3d.shared::cluster.global.mbarrier::complete_tx::bytes [%0], [%1, {%3, %4, %5}], [%2];"
               ::"r"(dst), "l"(tm), "r"(bar), "r"(c0), "r"(c1), "r"(c2) : "memory");
}
__device__ __forceinline__ void bulk_s2c(uint32_t dst, uint32_t src, uint32_t bytes, uint32_t bar) {
  asm volatile("cp.async.bulk.shared::cluster.shared::cta.mbarrier::complete_tx::bytes [%0], [%1], %2, [%3];"
               ::"r"(dst), "r"(src), "r"(bytes), "r"(bar) : "memory");
}
__device__ __forceinline__ void bulk_s2g(void* dst, uint32_t src, uint32_t bytes) {
  asm volatile("cp.async.bulk.global.shared::cta.bulk_group [%0], [%1], %2;" ::"l"(dst), "r"(src), "r"(bytes) : "memory");
}
__device__ __forceinline__ void st_async32(uint32_t dst, uint32_t v, uint32_t bar) {
  asm volatile("st.async.weak.shared::cluster.mbarrier::complete_tx::bytes.b32 [%0], %1, [%2];" ::"r"(dst), "r"(v), "r"(bar) : "memory");
}
__device__ __forceinline__ void ldsm4(uint32_t a, uint32_t& r0, uint32_t& r1, uint32_t& r2, uint32_t& r3) {
  asm volatile("ldmatrix.sync.aligned.m8n8.x4.shared.b16 {%0,%1,%2,%3}, [%4];" : "=r"(r0), "=r"(r1), "=r"(r2), "=r"(r3) : "r"(a) : "memory");
}
__device__ __forceinline__ void ldsm4t(uint32_t a, uint32_t& r0, uint32_t& r1, uint32_t& r2, uint32_t& r3) {
  asm volatile("ldmatrix.sync.aligned.m8n8.x4.trans.shared.b16 {%0,%1,%2,%3}, [%4];" : "=r"(r0), "=r"(r1), "=r"(r2), "=r"(r3) : "r"(a) : "memory");
}
__device__ __forceinline__ void stsm4(uint32_t a, uint32_t r0, uint32_t r1, uint32_t r2, uint32_t r3) {
  asm volatile("stmatrix.sync.aligned.m8n8.x4.shared.b16 [%0], {%1,%2,%3,%4};" ::"r"(a), "r"(r0), "r"(r1), "r"(r2), "r"(r3) : "memory");
}
__device__ __forceinline__ void stsm2(uint32_t a, uint32_t r0, uint32_t r1) {
  asm volatile("stmatrix.sync.aligned.m8n8.x2.shared.b16 [%0], {%1,%2};" ::"r"(a), "r"(r0), "r"(r1) : "memory");
}
__device__ __forceinline__ void stsm4t(uint32_t a, uint32_t r0, uint32_t r1, uint32_t r2, uint32_t r3) {
  asm volatile("stmatrix.sync.aligned.m8n8.x4.trans.shared.b16 [%0], {%1,%2,%3,%4};" ::"r"(a), "r"(r0), "r"(r1), "r"(r2), "r"(r3) : "memory");
}
__device__ __forceinline__ void mma16z(float (&c)[4], uint32_t a0, uint32_t a1, uint32_t a2, uint32_t a3, uint32_t b0, uint32_t b1) {
  asm volatile("mma.sync.aligned.m16n8k16.row.col.f32.bf16.bf16.f32 {%0,%1,%2,%3}, {%4,%5,%6,%7}, {%8,%9}, {%10,%10,%10,%10};"
               : "=f"(c[0]), "=f"(c[1]), "=f"(c[2]), "=f"(c[3]) : "r"(a0), "r"(a1), "r"(a2), "r"(a3), "r"(b0), "r"(b1), "f"(0.f));
}
__device__ __forceinline__ void mma16(float (&c)[4], uint32_t a0, uint32_t a1, uint32_t a2, uint32_t a3, uint32_t b0, uint32_t b1) {
  asm volatile("mma.sync.aligned.m16n8k16.row.col.f32.bf16.bf16.f32 {%0,%1,%2,%3}, {%4,%5,%6,%7}, {%8,%9}, {%0,%1,%2,%3};"
               : "+f"(c[0]), "+f"(c[1]), "+f"(c[2]), "+f"(c[3]) : "r"(a0), "r"(a1), "r"(a2), "r"(a3), "r"(b0), "r"(b1));
}
__device__ __forceinline__ void mma8(float (&c)[4], uint32_t a0, uint32_t a1, uint32_t b0) {
  asm volatile("mma.sync.aligned.m16n8k8.row.col.f32.bf16.bf16.f32 {%0,%1,%2,%3}, {%4,%5}, {%6}, {%0,%1,%2,%3};"
               : "+f"(c[0]), "+f"(c[1]), "+f"(c[2]), "+f"(c[3]) : "r"(a0), "r"(a1), "r"(b0));
}
__device__ __forceinline__ uint32_t pack2(float lo, float hi) {
  uint32_t r; asm("cvt.rn.bf16x2.f32 %0, %1, %2;" : "=r"(r) : "f"(hi), "f"(lo)); return r;
}
__device__ __forceinline__ float ex2(float x) { float r; asm("ex2.approx.ftz.f32 %0, %1;" : "=f"(r) : "f"(x)); return r; }
__device__ __forceinline__ void wg_fence() { asm volatile("wgmma.fence.sync.aligned;" ::: "memory"); }
__device__ __forceinline__ void wg_commit() { asm volatile("wgmma.commit_group.sync.aligned;" ::: "memory"); }
template <int N> __device__ __forceinline__ void wg_wait() { asm volatile("wgmma.wait_group.sync.aligned %0;" ::"n"(N) : "memory"); }
template <int TB>
__device__ __forceinline__ void wgmma_rs32(float (&d)[16], uint32_t a0, uint32_t a1, uint32_t a2, uint32_t a3, uint64_t desc, int acc) {
  asm volatile("{.reg .pred p; setp.ne.b32 p, %21, 0;\n"
               "wgmma.mma_async.sync.aligned.m64n32k16.f32.bf16.bf16 {%0,%1,%2,%3,%4,%5,%6,%7,%8,%9,%10,%11,%12,%13,%14,%15}, {%16,%17,%18,%19}, %20, p, 1, 1, %22;}"
               : "+f"(d[0]), "+f"(d[1]), "+f"(d[2]), "+f"(d[3]), "+f"(d[4]), "+f"(d[5]), "+f"(d[6]), "+f"(d[7]),
                 "+f"(d[8]), "+f"(d[9]), "+f"(d[10]), "+f"(d[11]), "+f"(d[12]), "+f"(d[13]), "+f"(d[14]), "+f"(d[15])
               : "r"(a0), "r"(a1), "r"(a2), "r"(a3), "l"(desc), "r"(acc), "n"(TB));
}
template <int TA, int TB>
__device__ __forceinline__ void wgmma_ss32(float (&d)[16], uint64_t adesc, uint64_t desc, int acc) {
  asm volatile("{.reg .pred p; setp.ne.b32 p, %18, 0;\n"
               "wgmma.mma_async.sync.aligned.m64n32k16.f32.bf16.bf16 {%0,%1,%2,%3,%4,%5,%6,%7,%8,%9,%10,%11,%12,%13,%14,%15}, %16, %17, p, 1, 1, %19, %20;}"
               : "+f"(d[0]), "+f"(d[1]), "+f"(d[2]), "+f"(d[3]), "+f"(d[4]), "+f"(d[5]), "+f"(d[6]), "+f"(d[7]),
                 "+f"(d[8]), "+f"(d[9]), "+f"(d[10]), "+f"(d[11]), "+f"(d[12]), "+f"(d[13]), "+f"(d[14]), "+f"(d[15])
               : "l"(adesc), "l"(desc), "r"(acc), "n"(TA), "n"(TB));
}
__device__ __forceinline__ void wgmma_ss40_tt(float (&d)[20], uint64_t adesc, uint64_t desc, int acc) {
  asm volatile("{.reg .pred p; setp.ne.b32 p, %22, 0;\n"
               "wgmma.mma_async.sync.aligned.m64n40k16.f32.bf16.bf16 {%0,%1,%2,%3,%4,%5,%6,%7,%8,%9,%10,%11,%12,%13,%14,%15,%16,%17,%18,%19}, %20, %21, p, 1, 1, 1, 1;}"
               : "+f"(d[0]), "+f"(d[1]), "+f"(d[2]), "+f"(d[3]), "+f"(d[4]), "+f"(d[5]), "+f"(d[6]), "+f"(d[7]),
                 "+f"(d[8]), "+f"(d[9]), "+f"(d[10]), "+f"(d[11]), "+f"(d[12]), "+f"(d[13]), "+f"(d[14]), "+f"(d[15]),
                 "+f"(d[16]), "+f"(d[17]), "+f"(d[18]), "+f"(d[19])
               : "l"(adesc), "l"(desc), "r"(acc));
}
__device__ __forceinline__ float rcp(float x) { float r; asm("rcp.approx.ftz.f32 %0, %1;" : "=f"(r) : "f"(x)); return r; }
__device__ __forceinline__ uint64_t make_desc(uint32_t addr, uint32_t lbo, uint32_t sbo, uint32_t swz) {
  return (uint64_t)((addr & 0x3FFFF) >> 4) | ((uint64_t)(lbo >> 4) << 16) | ((uint64_t)(sbo >> 4) << 32) | ((uint64_t)swz << 62);
}
__device__ __forceinline__ void ld_b128(const void* p, uint32_t& a, uint32_t& b, uint32_t& c, uint32_t& d) {
  asm volatile("{.reg .b128 t; .reg .b64 lo, hi; ld.relaxed.gpu.global.b128 t, [%4]; mov.b128 {lo, hi}, t; mov.b64 {%0,%1}, lo; mov.b64 {%2,%3}, hi;}"
               : "=r"(a), "=r"(b), "=r"(c), "=r"(d) : "l"(p) : "memory");
}
__device__ __forceinline__ void st_b128(void* p, uint32_t a, uint32_t b, uint32_t c, uint32_t d) {
  asm volatile("{.reg .b128 t; .reg .b64 lo, hi; mov.b64 lo, {%1,%2}; mov.b64 hi, {%3,%4}; mov.b128 t, {lo, hi}; st.relaxed.gpu.global.b128 [%0], t;}"
               ::"l"(p), "r"(a), "r"(b), "r"(c), "r"(d) : "memory");
}
__device__ __forceinline__ void ld_v4(const void* p, uint32_t& a, uint32_t& b, uint32_t& c, uint32_t& d) {
  asm volatile("ld.relaxed.gpu.global.v4.u32 {%0,%1,%2,%3}, [%4];" : "=r"(a), "=r"(b), "=r"(c), "=r"(d) : "l"(p) : "memory");
}
__device__ __forceinline__ void st_u32(void* p, uint32_t v) { asm volatile("st.relaxed.gpu.global.u32 [%0], %1;" ::"l"(p), "r"(v) : "memory"); }
__device__ __forceinline__ void sts128(uint32_t a, uint32_t x, uint32_t y, uint32_t z, uint32_t w) {
  asm volatile("st.shared.v4.u32 [%0], {%1,%2,%3,%4};" ::"r"(a), "r"(x), "r"(y), "r"(z), "r"(w) : "memory");
}
__device__ __forceinline__ void lds128f(uint32_t a, float& x, float& y, float& z, float& w) {
  asm volatile("ld.shared.v4.f32 {%0,%1,%2,%3}, [%4];" : "=f"(x), "=f"(y), "=f"(z), "=f"(w) : "r"(a) : "memory");
}
__device__ __forceinline__ void sts32f(uint32_t a, float x) { asm volatile("st.shared.f32 [%0], %1;" ::"r"(a), "f"(x) : "memory"); }
__device__ __forceinline__ void lds64f(uint32_t a, float& x, float& y) { asm volatile("ld.shared.v2.f32 {%0,%1}, [%2];" : "=f"(x), "=f"(y) : "r"(a) : "memory"); }

__device__ __forceinline__ void st_v2(void* p, uint32_t a, uint32_t b) { asm volatile("st.relaxed.gpu.global.v2.u32 [%0], {%1,%2};" ::"l"(p), "r"(a), "r"(b) : "memory"); }
__device__ __forceinline__ void ld_v2(const void* p, uint32_t& a, uint32_t& b) { asm volatile("ld.relaxed.gpu.global.v2.u32 {%0,%1}, [%2];" : "=r"(a), "=r"(b) : "l"(p) : "memory"); }
__device__ __forceinline__ uint32_t ld_u32(const void* p) { uint32_t v; asm volatile("ld.relaxed.gpu.global.u32 %0, [%1];" : "=r"(v) : "l"(p) : "memory"); return v; }
__device__ __forceinline__ void lds128(uint32_t a, uint32_t& x, uint32_t& y, uint32_t& z, uint32_t& w) {
  asm volatile("ld.shared.v4.u32 {%0,%1,%2,%3}, [%4];" : "=r"(x), "=r"(y), "=r"(z), "=r"(w) : "r"(a) : "memory");
}
__device__ __forceinline__ void lds64(uint32_t a, uint32_t& x, uint32_t& y) { asm volatile("ld.shared.v2.u32 {%0,%1}, [%2];" : "=r"(x), "=r"(y) : "r"(a) : "memory"); }
__device__ __forceinline__ uint32_t lds32(uint32_t a) { uint32_t v; asm volatile("ld.shared.u32 %0, [%1];" : "=r"(v) : "r"(a) : "memory"); return v; }
__device__ __forceinline__ void sts32(uint32_t a, uint32_t v) { asm volatile("st.shared.u32 [%0], %1;" ::"r"(a), "r"(v) : "memory"); }
__device__ __forceinline__ void sts64(uint32_t a, uint32_t x, uint32_t y) { asm volatile("st.shared.v2.u32 [%0], {%1,%2};" ::"r"(a), "r"(x), "r"(y) : "memory"); }
__device__ __forceinline__ uint32_t clk() { uint64_t c; asm volatile("mov.u64 %0, %%clock64;" : "=l"(c)::"memory"); return (uint32_t)c; }
__device__ __forceinline__ uint32_t gtime() { uint64_t c; asm volatile("mov.u64 %0, %%globaltimer;" : "=l"(c)::"memory"); return (uint32_t)c; }
__device__ __forceinline__ uint32_t gtime_after(uint32_t dep) {
  uint32_t t;
  asm volatile("{.reg .pred p; .reg .u64 c; setp.ne.u32 p, %1, 0x7fc12345; mov.u64 c, 0; @p mov.u64 c, %%globaltimer; cvt.u32.u64 %0, c;}" : "=r"(t) : "r"(dep) : "memory");
  return t;
}
__device__ __forceinline__ void spin_clk_until(uint32_t t) { while ((int)(clk() - t) < 0) {} }
__device__ __forceinline__ void spin_gt_until(uint32_t t) { while ((int)(gtime() - t) < 0) {} }
template <int L> __device__ __forceinline__ uint32_t lop3(uint32_t a, uint32_t b, uint32_t c) {
  uint32_t r; asm("lop3.b32 %0, %1, %2, %3, %4;" : "=r"(r) : "r"(a), "r"(b), "r"(c), "n"(L)); return r;
}
__device__ __forceinline__ float bf_lo(uint32_t w) { return __uint_as_float(w << 16); }
__device__ __forceinline__ float bf_hi(uint32_t w) { return __uint_as_float(w & 0xffff0000u); }
__device__ __forceinline__ uint32_t near_page(unsigned char* p) {
  int ba = 1 << 30, bb = 1 << 30;
  for (int r = 0; r < 5; r++) {
    const uint32_t t0 = clk();
    uint32_t u, v, t1, t2;
    asm volatile("atom.relaxed.gpu.global.exch.b32 %0, [%1], %2;" : "=r"(u) : "l"(p), "r"(r) : "memory");
    asm volatile("atom.relaxed.gpu.global.exch.b32 %0, [%1], %2;" : "=r"(v) : "l"(p + 4096), "r"(r) : "memory");
    asm volatile("{.reg .pred p; .reg .u64 c; setp.ne.u32 p, %1, 0x7fc12345; mov.u64 c, 0; @p mov.u64 c, %%clock64; cvt.u32.u64 %0, c;}" : "=r"(t1) : "r"(u) : "memory");
    asm volatile("{.reg .pred p; .reg .u64 c; setp.ne.u32 p, %1, 0x7fc12345; mov.u64 c, 0; @p mov.u64 c, %%clock64; cvt.u32.u64 %0, c;}" : "=r"(t2) : "r"(v) : "memory");
    ba = min(ba, (int)(t1 - t0));
    bb = min(bb, (int)(t2 - t0));
  }
  return bb - ba > 80 ? 0u : 4096u;
}

#define K_SPLIT 5
#define K_GATE 15
#define D1 192
#define T_DELAY 0
#define T_BAR 3
#define DANC 800
#define D2 60
namespace rk {
constexpr uint32_t XT = 0;
constexpr uint32_t RA = 65536;
constexpr uint32_t KV = RA;
constexpr uint32_t QX = KV + 4 * 20480;
constexpr uint32_t WRES = RA + 14 * 8192;
constexpr uint32_t WOS = RA + 131072;
constexpr uint32_t OST = WOS;
constexpr uint32_t PS = WOS + 8192;
constexpr uint32_t MEMS = WOS + 16384;
constexpr uint32_t QM = MEMS + 8192;
constexpr uint32_t SC = QM + 2048;
constexpr uint32_t SR = SC + 2048;
constexpr uint32_t VM = QX;
constexpr uint32_t BAR = SR + 1024;
constexpr uint32_t B_QKV = BAR;
constexpr uint32_t B_KV = BAR + 8;
constexpr uint32_t B_XF = BAR + 40;
constexpr uint32_t B_W = BAR + 56;
constexpr uint32_t B_FREE = BAR + 88;
constexpr uint32_t B_OF = BAR + 96, B_OE = BAR + 104, B_PUB = BAR + 112;
constexpr uint32_t TK = BAR + 128;
constexpr uint32_t TABS = BAR + 256;
constexpr uint32_t TM = BAR + 768;
constexpr uint32_t SMEM = TM + 4096 + 1024;
constexpr int NB_P = 1, NB_T = 2, NB_MEM = 3, NB_S = 4, NB_TD = 5, NB_TAB = 6, NB_V = 7, NB_M = 8;
constexpr float kExpScale = 0.08838834764831845f * 1.4426950408889634f;
constexpr int kSplit = K_SPLIT;
constexpr int kGate = K_GATE;
}

__device__ __forceinline__ void r_proj_issue(const uint32_t (&w)[112], float (&d)[16], uint32_t sb, int seg, int warp, int j0, int j1) {
  using namespace rk;
  const uint64_t desc = make_desc(sb + XT + (seg & 1) * 32768, 16, 1024, 1);
  const uint64_t adesc = make_desc(sb + WRES + (warp >> 2) * 8192, 1024, 1024, 1);
  wg_fence();
#pragma unroll
  for (int i = 0; i < 32; i++) {
    if (i < j0 || i >= j1) continue;
    const int j = i < 8 ? i : (i - 8) % 6 == 0 ? 28 + (i - 8) / 6 : i - 1 - (i - 8) / 6;
    const uint64_t bd = desc + (uint64_t)(((j >> 2) * 4096 + (j & 3) * 32) >> 4);
    if (j < 28) wgmma_rs32<0>(d, w[4 * j], w[4 * j + 1], w[4 * j + 2], w[4 * j + 3], bd, j > 0);
    else wgmma_ss32<1, 0>(d, adesc + (uint64_t)((j - 28) * 128), bd, 1);
  }
  wg_commit();
}
__device__ __forceinline__ uint32_t r_proj_dst(int seg, uint32_t rank) {
  using namespace rk;
  return rank == 0 ? QX + (seg & 3) * 8192 : KV + (seg & 3) * 20480 + (rank - 1) * 10240;
}
__device__ __forceinline__ void r_proj_store(const float (&d)[16], uint32_t sb, int seg, int warp, int lane, uint32_t rank) {
  const uint32_t a = sb + r_proj_dst(seg, rank) + (lane >> 4) * 2048 + (16 * warp + (lane & 15)) * 16;
  stsm4(a, pack2(d[0], d[1]), pack2(d[2], d[3]), pack2(d[4], d[5]), pack2(d[6], d[7]));
  stsm4(a + 4096, pack2(d[8], d[9]), pack2(d[10], d[11]), pack2(d[12], d[13]), pack2(d[14], d[15]));
  fence_async_smem();
}
__device__ __forceinline__ void r_proj_share(uint32_t sb, int seg, uint32_t rank) {
  using namespace rk;
  const uint32_t bar = sb + B_KV + 8 * (seg & 3), src = sb + r_proj_dst(seg, rank);
  if (rank != 0) {
    bulk_s2c(mapa(src, 3 - rank), src, 8192, mapa(bar, 3 - rank));
    bulk_s2c(mapa(src, 0), src, 8192, mapa(bar, 0));
  }
  mbar_arrive_tx(bar, rank == 0 ? 16384 : 8192);
}
__device__ __forceinline__ void r_store_o(uint32_t sb, int seg, uint32_t head, int& budget) {
  using namespace rk;
  mbar_wait(sb + B_OF, seg & 1, budget);
  bf16* dst = g_o + (size_t)((seg >> 2) * 64 + head * 2) * 8192 + (seg & 3) * 2048;
  bulk_s2g(dst, sb + OST, 4096);
  bulk_s2g(dst + 8192, sb + OST + 4096, 4096);
  asm volatile("cp.async.bulk.commit_group;" ::: "memory");
}
__device__ __forceinline__ void r_flag_o(int seg) {
  asm volatile("cp.async.bulk.wait_group 0; red.relaxed.gpu.global.add.u32 [%0], 1;" ::"l"(&g_cnt[C_O + (seg >> 2)]) : "memory");
}

template <int I>
__device__ __forceinline__ void r_vo_issue(const uint32_t (&wo)[64], float (&d)[16], uint32_t sb, int seg) {
  using namespace rk;
  const uint64_t desc = make_desc(sb + KV + (seg & 3) * 20480 + 10240, 128, 2048, 0);
  const uint64_t adesc = make_desc(sb + WOS, 16, 1024, 1);
  wg_fence();
#pragma unroll
  for (int kk = 0; kk < 8; kk++) {
    if (I < 2) wgmma_rs32<1>(d, wo[32 * I + 4 * kk], wo[32 * I + 4 * kk + 1], wo[32 * I + 4 * kk + 2], wo[32 * I + 4 * kk + 3], desc + (uint64_t)(kk * 16), kk > 0);
    else wgmma_ss32<0, 1>(d, adesc + (uint64_t)(((kk >> 2) * 8192 + (kk & 3) * 32) >> 4), desc + (uint64_t)(kk * 16), kk > 0);
  }
  wg_commit();
}
__device__ __forceinline__ void r_vo_issue2(const uint32_t (&wo)[64], float (&d0)[16], float (&d2)[16], uint32_t sb, int seg) {
  using namespace rk;
  const uint64_t desc = make_desc(sb + KV + (seg & 3) * 20480 + 10240, 128, 2048, 0);
  const uint64_t adesc = make_desc(sb + WOS, 16, 1024, 1);
  wg_fence();
#pragma unroll
  for (int kk = 0; kk < 8; kk++) {
    wgmma_rs32<1>(d0, wo[4 * kk], wo[4 * kk + 1], wo[4 * kk + 2], wo[4 * kk + 3], desc + (uint64_t)(kk * 16), kk > 0);
    wgmma_ss32<0, 1>(d2, adesc + (uint64_t)(((kk >> 2) * 8192 + (kk & 3) * 32) >> 4), desc + (uint64_t)(kk * 16), kk > 0);
  }
  wg_commit();
}
__device__ __forceinline__ void pack16(uint32_t* o, const float (&d)[16]) {
#pragma unroll
  for (int j = 0; j < 8; j++) o[j] = pack2(d[2 * j], d[2 * j + 1]);
}

template <int NT, bool CHECK>
__device__ __forceinline__ bool r_mem_out(uint32_t vma, const uint32_t (&p)[5], const uint32_t (&vox)[8 * NT], const uint32_t (&vp)[4],
                                          uint64_t (&mail)[NT], uint32_t tag) {
  using namespace rk;
  constexpr uint32_t kOnes = 0x3F803F80u;
  float o[NT][4], sum[4];
  mma16z(sum, kOnes, kOnes, kOnes, kOnes, p[0], p[1]);
#pragma unroll
  for (int i = 0; i < NT; i++) mma16z(o[i], vox[8 * i], vox[8 * i + 1], vox[8 * i + 2], vox[8 * i + 3], p[0], p[1]);
  if (NT == 3 && CHECK) bar_sync_after(NB_V, 256, __float_as_uint(o[NT - 1][0]));
  mma16(sum, kOnes, kOnes, kOnes, kOnes, p[2], p[3]);
#pragma unroll
  for (int i = 0; i < NT; i++) mma16(o[i], vox[8 * i + 4], vox[8 * i + 5], vox[8 * i + 6], vox[8 * i + 7], p[2], p[3]);
  uint64_t v3 = 0;
  if (NT == 3) {
    asm volatile("ld.shared.v2.u64 {%0,%1}, [%2];" : "=l"(mail[NT - 1]), "=l"(v3) : "r"(vma + 2048) : "memory");
    asm volatile("ld.shared.v2.u64 {%0,%1}, [%2];" : "=l"(mail[0]), "=l"(mail[1]) : "r"(vma) : "memory");
  }
  mma8(sum, kOnes, kOnes, p[4]);
  mma8(o[0], vp[0], vp[1], p[4]);
  mma8(o[1], vp[2], vp[3], p[4]);
  if (NT == 3) mma8(o[NT - 1], (uint32_t)v3, (uint32_t)(v3 >> 32), p[4]);
  const float i0 = rcp(sum[0]), i1 = rcp(sum[1]);
  const bool ok = !CHECK || __all_sync(~0u, max(__float_as_uint(sum[0]) - 0x30000000u, __float_as_uint(sum[1]) - 0x30000000u) < 0x1F000000u);
#pragma unroll
  for (int i = 0; i < NT; i++)
    asm volatile("{.reg .pred q; setp.ne.u32 q, %3, 0; @q st.relaxed.gpu.global.v2.u32 [%0], {%1,%2};}" ::"l"(mail[i]),
                 "r"(lop3<0xea>(pack2(o[i][0] * i0, o[i][2] * i0), ~1u, tag)), "r"(pack2(o[i][1] * i1, o[i][3] * i1)), "r"((uint32_t)ok) : "memory");
  return ok;
}
__device__ __forceinline__ void r_mem_scores(uint32_t a, float& u0, float& u1) {
  float u[8];
  lds128f(a + 512, u[0], u[1], u[2], u[3]);
  lds128f(a + 1024, u[4], u[5], u[6], u[7]);
  u0 = (u[0] + u[2]) + (u[4] + u[6]);
  u1 = (u[1] + u[3]) + (u[5] + u[7]);
}

template <int NT>
__device__ __forceinline__ void r_attn_role(uint32_t sb, int tw, int lane, uint32_t rank, uint32_t head, const bf16* __restrict__ Wo, int& budget) {
  using namespace rk;
  const int g = lane >> 2, t = lane & 3;
  const int tile0 = (NT == 2 ? 0 : 12 * (int)rank - 4) + tw;
  uint32_t wo[64];
  const uint32_t woa = sb + WOS + (16 * tw + (lane & 15)) * 128;
  const uint32_t wx = (lane >> 4) ^ (lane & 7);
  {
    uint32_t wt[32 * NT];
#pragma unroll
    for (int i = 0; i < NT; i++) {
      const uint32_t* src = reinterpret_cast<const uint32_t*>(Wo + (size_t)(head * 128 + 2 * t) * kD + (tile0 + 4 * i) * 16 + 2 * g);
#pragma unroll
      for (int kk = 0; kk < 8; kk++) {
        wt[32 * i + 4 * kk] = __ldg(src + (16 * kk) * (kD / 2));
        wt[32 * i + 4 * kk + 1] = __ldg(src + (16 * kk + 1) * (kD / 2));
        wt[32 * i + 4 * kk + 2] = __ldg(src + (16 * kk + 8) * (kD / 2));
        wt[32 * i + 4 * kk + 3] = __ldg(src + (16 * kk + 9) * (kD / 2));
      }
    }
#pragma unroll
    for (int j = 0; j < 16 * NT; j++) {
      const uint32_t x = wt[2 * j], y = wt[2 * j + 1];
      wt[2 * j] = __byte_perm(x, y, 0x5410);
      wt[2 * j + 1] = __byte_perm(x, y, 0x7632);
    }
#pragma unroll
    for (int j = 0; j < 64; j++) wo[j] = wt[j];
    if (NT == 3) {
#pragma unroll
      for (int kk = 0; kk < 8; kk++)
        stsm4(woa + (kk >> 2) * 8192 + (((2 * (kk & 3)) ^ wx) << 4), wt[32 * NT - 32 + 4 * kk], wt[32 * NT - 31 + 4 * kk], wt[32 * NT - 30 + 4 * kk], wt[32 * NT - 29 + 4 * kk]);
    } else if (tw == 0) {
      sts128(sb + PS + 5 * 512 + lane * 16, 0u, 0u, 0u, 0u);
    }
    fence_async_smem();
    bar_sync(NB_T, 128);
  }
  uint64_t mail[NT];
  bar_sync(NB_TAB, 512);
#pragma unroll
  for (int i = 0; i < NT; i++) {
    const uint32_t unit = (tile0 + 4 * i) * 4 + (g >> 2) * 2 + (t >> 1);
    mail[i] = (uint64_t)(g_mail + (unit * 8192 + (lds32(sb + TABS + unit * 4) & 4096u) + head * 64 + (t & 1) * 32 + (g & 3) * 8));
  }
  uint32_t vox[8 * NT];
  uint32_t la = sb + lane * 16;
  OPAQUE(la);
  const uint32_t vma = la + VM + tw * 512;
  mbar_wait(sb + B_KV, 0, budget);
  if (NT == 3) {
    sts128(vma, (uint32_t)mail[0], (uint32_t)(mail[0] >> 32), (uint32_t)mail[1], (uint32_t)(mail[1] >> 32));
    sts64(vma + 2048, (uint32_t)mail[NT - 1], (uint32_t)(mail[NT - 1] >> 32));
  }
  {
    float d[16];
    r_vo_issue<0>(wo, d, sb, 0); wg_wait<0>(); pack16(vox, d);
    r_vo_issue<1>(wo, d, sb, 0); wg_wait<0>(); pack16(vox + 8, d);
    if (NT == 3) { r_vo_issue<2>(wo, d, sb, 0); wg_wait<0>(); pack16(vox + 8 * NT - 8, d); }
  }
  for (int s = 0;; s++) {
    if (s < kNSeg) {
      const uint32_t va = la + KV + (s & 3) * 20480 + 10240 + 8192;
      float vm[4][4];
      uint32_t b[16];
      mbar_wait(sb + B_QKV, s & 1, budget);
#pragma unroll
      for (int k2 = 0; k2 < 4; k2++) ldsm4t(va + k2 * 512, b[4 * k2], b[4 * k2 + 1], b[4 * k2 + 2], b[4 * k2 + 3]);
      TMARKD(tw == 0, 3, b[0]);
#pragma unroll
      for (int kk = 0; kk < 4; kk++) {
#pragma unroll
        for (int c = 0; c < 4; c++) {
          const uint32_t* p = &wo[16 * c + 4 * kk];
          const uint32_t* q = &b[8 * (c & 1) + 2 * kk];
          if (kk == 0) mma16z(vm[c], p[0], p[1], p[2], p[3], q[0], q[1]);
          else mma16(vm[c], p[0], p[1], p[2], p[3], q[0], q[1]);
        }
      }
      uint32_t p[5], vp[4];
#pragma unroll
      for (int i = 0; i < 2; i++) {
        vp[2 * i] = pack2(vm[2 * i][0] + vm[2 * i + 1][0], vm[2 * i][1] + vm[2 * i + 1][1]);
        vp[2 * i + 1] = pack2(vm[2 * i][2] + vm[2 * i + 1][2], vm[2 * i][3] + vm[2 * i + 1][3]);
      }
      bar_sync_after(NB_S, 256, vp[0] | vp[1] | vp[2] | vp[3]);
      lds128(la + SC, p[0], p[1], p[2], p[3]);
      TMARKD(tw == 0, 4, p[0]);
      float u0, u1;
      r_mem_scores(la + SC, u0, u1);
      p[4] = pack2(ex2(u0 * kExpScale), ex2(u1 * kExpScale));
      const uint32_t tag = (s + 1) & 1;
      const bool ok = r_mem_out<NT, true>(vma, p, vox, vp, mail, tag);
      bar_arrive(NB_TD, 384);
      sts32(sb + TK + 48 + tw * 4, gtime_after(p[4]));
      TMARKD(tw == 0, 5, ok);
      if (!ok) {
        float sv[4][2];
#pragma unroll
        for (int j = 0; j < 4; j++) lds64f(sb + SR + j * 256 + lane * 8, sv[j][0], sv[j][1]);
        r_mem_scores(la + SC, u0, u1);
        float m = fmaxf(fmaxf(fmaxf(sv[0][0], sv[0][1]), fmaxf(sv[1][0], sv[1][1])), fmaxf(fmaxf(sv[2][0], sv[2][1]), fmaxf(sv[3][0], sv[3][1])));
        m = fmaxf(m, fmaxf(u0, u1));
        m = fmaxf(m, __shfl_xor_sync(~0u, m, 1));
        const float mb = -fmaxf(m, __shfl_xor_sync(~0u, m, 2)) * kExpScale;
#pragma unroll
        for (int j = 0; j < 4; j++) p[j] = pack2(ex2(fmaf(sv[j][0], kExpScale, mb)), ex2(fmaf(sv[j][1], kExpScale, mb)));
        p[4] = pack2(ex2(fmaf(u0, kExpScale, mb)), ex2(fmaf(u1, kExpScale, mb)));
        r_mem_out<NT, false>(vma, p, vox, vp, mail, tag);
      }
      if (tw == 0 && lane == 0) mbar_arrive_tx(sb + B_QKV, 4096);
    } else {
      bar_sync(NB_T, 128);
    }
    if (NT == 3) {
      if (s + 1 == kNSeg) break;
      mbar_wait(sb + B_KV + 8 * ((s + 1) & 3), ((s + 1) >> 2) & 1, budget);
      float d0[16], d1[16];
      r_vo_issue2(wo, d0, d1, sb, s + 1);
      wg_wait<0>();
      pack16(vox, d0);
      r_vo_issue<1>(wo, d0, sb, s + 1);
      pack16(vox + 8 * NT - 8, d1);
      wg_wait<0>();
      pack16(vox + 8, d0);
    } else {
      float sc[20], d0[16], d1[16];
      {
        const uint32_t vb = sb + KV + ((s - 1) & 3) * 20480 + 10240;
        const uint64_t pd = make_desc(sb + PS, 512, 128, 0);
        const uint64_t vd = make_desc(vb, 2048, 128, 0), vd2 = make_desc(vb + 8192, 0, 128, 0);
        wg_fence();
        wgmma_ss32<0, 0>(d0, vd, pd, 0);
        wgmma_ss32<0, 0>(d1, vd + 64, pd, 0);
        wgmma_ss32<0, 0>(d0, vd + 256, pd + 64, 1);
        wgmma_ss32<0, 0>(d1, vd + 256 + 64, pd + 64, 1);
        wgmma_ss32<0, 0>(d0, vd2, pd + 128, 1);
        wgmma_ss32<0, 0>(d1, vd2 + 64, pd + 128, 1);
        wg_commit();
      }
      const uint32_t oa = sb + OST + ((lane >> 4) * 8 + (lane & 7)) * 128 + (((2 * tw + ((lane >> 3) & 1)) ^ (lane & 7)) << 4);
      if (s > 1) mbar_wait(sb + B_OE, s & 1, budget);
      wg_wait<0>();
      stsm4t(oa, pack2(d0[0], d0[1]), pack2(d0[2], d0[3]), pack2(d0[4], d0[5]), pack2(d0[6], d0[7]));
      stsm4t(oa + 2048, pack2(d0[8], d0[9]), pack2(d0[10], d0[11]), pack2(d0[12], d0[13]), pack2(d0[14], d0[15]));
      stsm4t(oa + 4096, pack2(d1[0], d1[1]), pack2(d1[2], d1[3]), pack2(d1[4], d1[5]), pack2(d1[6], d1[7]));
      stsm4t(oa + 6144, pack2(d1[8], d1[9]), pack2(d1[10], d1[11]), pack2(d1[12], d1[13]), pack2(d1[14], d1[15]));
      fence_async_smem();
      __syncwarp();
      if (lane == 0 && s) mbar_arrive(sb + B_OF);
      if (s == kNSeg) break;
      if (s + 1 < kNSeg) mbar_wait(sb + B_KV + 8 * ((s + 1) & 3), ((s + 1) >> 2) & 1, budget);
      {
        const uint64_t qd = make_desc(sb + QX + (s & 3) * 8192, 128, 2048, 0), kd = make_desc(sb + KV + (s & 3) * 20480, 128, 2048, 0);
        const uint64_t vd = make_desc(sb + KV + ((s + 1) & 3) * 20480 + 10240, 128, 2048, 0);
        wg_fence();
#pragma unroll
        for (int kk = 0; kk < 8; kk++) {
          wgmma_ss40_tt(sc, qd + (uint64_t)(kk * 16), kd + (uint64_t)(kk * 16), kk > 0);
          wgmma_rs32<1>(d0, wo[4 * kk], wo[4 * kk + 1], wo[4 * kk + 2], wo[4 * kk + 3], vd + (uint64_t)(kk * 16), kk > 0);
        }
        wg_commit();
      }
      wg_wait<0>();
      pack16(vox, d0);
      r_vo_issue<1>(wo, d0, sb, s + 1);
      if (tw < 2) {
        const int dl = 16 * tw + g - 2 * t;
        float m0 = fmaxf(sc[16], sc[17]), m1 = fmaxf(sc[18], sc[19]);
#pragma unroll
        for (int n = 0; n < 4; n++) {
          if (8 * n > dl) sc[4 * n] = -INFINITY;
          if (8 * n + 1 > dl) sc[4 * n + 1] = -INFINITY;
          if (8 * n - 8 > dl) sc[4 * n + 2] = -INFINITY;
          if (8 * n - 7 > dl) sc[4 * n + 3] = -INFINITY;
          m0 = fmaxf(m0, fmaxf(sc[4 * n], sc[4 * n + 1]));
          m1 = fmaxf(m1, fmaxf(sc[4 * n + 2], sc[4 * n + 3]));
        }
        m0 = fmaxf(m0, __shfl_xor_sync(~0u, m0, 1)); m1 = fmaxf(m1, __shfl_xor_sync(~0u, m1, 1));
        m0 = fmaxf(m0, __shfl_xor_sync(~0u, m0, 2)); m1 = fmaxf(m1, __shfl_xor_sync(~0u, m1, 2));
        m0 *= -kExpScale; m1 *= -kExpScale;
        float s0 = 0.f, s1 = 0.f;
#pragma unroll
        for (int n = 0; n < 5; n++) {
          sc[4 * n] = ex2(fmaf(sc[4 * n], kExpScale, m0)); sc[4 * n + 1] = ex2(fmaf(sc[4 * n + 1], kExpScale, m0));
          sc[4 * n + 2] = ex2(fmaf(sc[4 * n + 2], kExpScale, m1)); sc[4 * n + 3] = ex2(fmaf(sc[4 * n + 3], kExpScale, m1));
          s0 += sc[4 * n] + sc[4 * n + 1]; s1 += sc[4 * n + 2] + sc[4 * n + 3];
        }
        s0 += __shfl_xor_sync(~0u, s0, 1); s1 += __shfl_xor_sync(~0u, s1, 1);
        s0 += __shfl_xor_sync(~0u, s0, 2); s1 += __shfl_xor_sync(~0u, s1, 2);
        const float i0 = rcp(s0), i1 = rcp(s1);
        uint32_t p[10];
#pragma unroll
        for (int n = 0; n < 5; n++) { p[2 * n] = pack2(sc[4 * n] * i0, sc[4 * n + 1] * i0); p[2 * n + 1] = pack2(sc[4 * n + 2] * i1, sc[4 * n + 3] * i1); }
        const uint32_t pa = sb + PS + (lane >> 4) * 512 + (16 * tw + (lane & 15)) * 16;
        if (s) mbar_wait(sb + B_OF, (s - 1) & 1, budget);
        stsm4(pa, p[0], p[1], p[2], p[3]);
        stsm4(pa + 1024, p[4], p[5], p[6], p[7]);
        stsm2(pa + 2048, p[8], p[9]);
        fence_async_smem();
      }
      TMARKD(tw == 0, 18, 0);
      wg_wait<0>();
      pack16(vox + 8, d0);
    }
    TMARKD(tw == 0, 6, vox[8 * NT - 1]);
  }
}

template <bool V3>
__device__ __forceinline__ void r_poll_role(uint32_t sb, int mw, int lane, uint32_t unit) {
  using namespace rk;
  int budget = 1 << 20;
  uint32_t span = 0, tp = 0;
  bar_sync(NB_MEM, 384);
  for (int s = 0;; s++) {
    uint32_t an[3] = {0u, 0u, 0u};
    const uint32_t k0 = clk(), t0 = gtime();
    {
      uint32_t ln = lane;
      OPAQUE(ln);
      const uint32_t rot = mw * 512;
      const uint32_t ka = sb + KV + (s & 3) * 20480 + ln * 16;
      const uint32_t qa = sb + QM + (((ln >> 3) & 1) * 2 + (ln >> 4)) * 128 + (ln & 7) * 16;
      const uint32_t woa = sb + WOS + (16 * mw + (ln & 15)) * 128 + (((ln >> 4) ^ (ln & 7)) << 4);
      if (mw == 3) {
        uint32_t n0, n1;
        lds64(sb + TK, n0, n1);
        uint32_t e[4];
        lds128(sb + TK + 48, e[0], e[1], e[2], e[3]);
        const uint32_t last = max(max(e[0] - tp, e[1] - tp), max(e[2] - tp, e[3] - tp)) + D1;
        span = s < 4 || (s & 7) == 0 ? last : min(span, last);
        tp = t0;
        if (ln == 0 && s) st_u32(&g_anc[blockIdx.x], (t0 + span) | max(n0, n1));
        spin_clk_until(k0 + DANC);
#pragma unroll
        for (int i = 0; i < 3; i++) an[i] = ld_u32(&g_anc[i * 32 + ln]);
      }
      mbar_wait(sb + B_KV + 8 * (s & 3), (s >> 2) & 1, budget);
      uint32_t kf[16], q[16], km[4];
#pragma unroll
      for (int i = 0; i < 4; i++) ldsm4t(ka + rot * 4 + (rot ^ (i * 512)), kf[4 * i], kf[4 * i + 1], kf[4 * i + 2], kf[4 * i + 3]);
      mbar_wait(sb + B_QKV, s & 1, budget);
      ldsm4t(qa + rot, q[0], q[1], q[2], q[3]);
      ldsm4t(qa + (rot ^ 1024), q[8], q[9], q[10], q[11]);
      ldsm4t(qa + (rot ^ 512), q[4], q[5], q[6], q[7]);
      ldsm4t(qa + (rot ^ 1536), q[12], q[13], q[14], q[15]);
      ldsm4t(ka + 8192 + rot, km[0], km[1], km[2], km[3]);
      float c0[4], c1[4], c2[4], c3[4], cm0[4], cm1[4];
      mma16z(c0, q[0], q[1], q[2], q[3], kf[0], kf[1]);
      mma16z(c1, q[0], q[1], q[2], q[3], kf[2], kf[3]);
      mma16z(c2, q[8], q[9], q[10], q[11], kf[8], kf[9]);
      mma16z(c3, q[8], q[9], q[10], q[11], kf[10], kf[11]);
      mma16(c0, q[4], q[5], q[6], q[7], kf[4], kf[5]);
      mma16(c1, q[4], q[5], q[6], q[7], kf[6], kf[7]);
      mma16(c2, q[12], q[13], q[14], q[15], kf[12], kf[13]);
      mma16(c3, q[12], q[13], q[14], q[15], kf[14], kf[15]);
      mma16z(cm0, q[0], q[1], q[2], q[3], km[0], km[1]);
      mma16z(cm1, q[0], q[1], q[2], q[3], km[2], km[3]);
      uint32_t a[8][4], b[16];
      auto ldv = [&](int h) {
#pragma unroll
        for (int kk = 4 * h; kk < 4 * h + 4; kk++) {
          if (!(kk & 1)) ldsm4t(ka + 10240 + 8192 + kk * 256, b[2 * kk], b[2 * kk + 1], b[2 * kk + 2], b[2 * kk + 3]);
          ldsm4((woa ^ ((kk & 3) << 5)) + h * 8192, a[kk][0], a[kk][1], a[kk][2], a[kk][3]);
        }
      };
      if (V3) ldv(0);
      const float s0 = (c0[0] + c1[2]) + (c2[0] + c3[2]), s1 = (c0[1] + c1[3]) + (c2[1] + c3[3]);
      sts64(sb + SR + mw * 256 + ln * 8, __float_as_uint(s0), __float_as_uint(s1));
      const uint32_t pw = pack2(ex2(s0 * kExpScale), ex2(s1 * kExpScale));
      sts64(sb + SC + 512 + (mw >> 1) * 512 + (mw & 1) * 8 + ln * 16, __float_as_uint(cm0[0] + cm1[2]), __float_as_uint(cm0[1] + cm1[3]));
      sts32(sb + SC + mw * 4 + ln * 16, pw);
      bar_arrive(NB_S, 256);
      TMARKD(mw == 0, 13, 0);
      if (V3) {
#pragma unroll
        for (int i = 0; i < 4; i++) b[2 * i] = lop3<0xf8>(b[2 * i], pw, blockIdx.y);
        ldv(1);
        mma16z(c0, a[0][0], a[0][1], a[0][2], a[0][3], b[0], b[1]);
        mma16z(c1, a[1][0], a[1][1], a[1][2], a[1][3], b[2], b[3]);
        mma16z(c2, a[2][0], a[2][1], a[2][2], a[2][3], b[4], b[5]);
        mma16z(c3, a[3][0], a[3][1], a[3][2], a[3][3], b[6], b[7]);
        mma16(c0, a[4][0], a[4][1], a[4][2], a[4][3], b[8], b[9]);
        mma16(c1, a[5][0], a[5][1], a[5][2], a[5][3], b[10], b[11]);
        mma16(c2, a[6][0], a[6][1], a[6][2], a[6][3], b[12], b[13]);
        mma16(c3, a[7][0], a[7][1], a[7][2], a[7][3], b[14], b[15]);
        sts64(sb + VM + 2048 + 8 + mw * 512 + ln * 16, pack2((c0[0] + c1[0]) + (c2[0] + c3[0]), (c0[1] + c1[1]) + (c2[1] + c3[1])),
              pack2((c0[2] + c1[2]) + (c2[2] + c3[2]), (c0[3] + c1[3]) + (c2[3] + c3[3])));
        bar_arrive(NB_V, 256);
        TMARKD(mw == 0, 19, 0);
      }
    }
    if (mw == 3) {
      int r = 0;
#pragma unroll
      for (int i = 0; i < 3; i++) { const int dt = an[i] - t0; r = max(r, dt < 4096 ? dt : 0); }
      const uint32_t x1 = t0 + (__reduce_max_sync(~0u, r) & ~31);
      sts64(sb + TK + 8, x1, x1 + 32 * __reduce_max_sync(~0u, max(max(an[0] & 31u, an[1] & 31u), an[2] & 31u)));
      TMARKD(1, 17, x1);
    }
    uint32_t ln = lane;
    OPAQUE(ln);
    const uint32_t so = (s & 1) * 32768;
    const unsigned char* mb = g_mail + (unit * 8192 + (lds32(sb + TABS + unit * 4) & 4096u) + (ln & 3) * 64 + (ln >> 2) * 8);
    unsigned char* pwp = g_pub + ((unit >> 5) * 8192 + (unit & 31) * 64 + so + ((ln >> 1) & 1) * 4096 + ((ln >> 4) * 2 + (ln & 1)) * 16 + ((ln >> 2) & 3) * 4);
    const unsigned char* pp = g_pub + (so + mw * 8192 + lds32(sb + TK + 16 + (s & 1) * 16 + mw * 4) + ln * 16);
    const uint32_t sel = (ln & 4) ? 0x3F800000u : 0x3F80u;
    const uint32_t ms = sb + MEMS + mw * 2048 + ln * 16;
    if (s + 1 == kNSeg) break;
    bar_sync(NB_M, 128);
    uint32_t x1, x2;
    lds64(sb + TK + 8, x1, x2);
    TMARKV(mw == 0, 20, x1); TMARKV(mw == 0, 21, x2);
    if (V3 && mw < 2) {
      const uint32_t tagm = (s & 1) ? 0u : ~0u;
      spin_gt_until(x1);
      TMARKD(mw == 0, 16, 0);
      for (int it = 0;; it++) {
        x1 = gtime();
        uint32_t x[16];
#pragma unroll
        for (int i = 0; i < 8; i++) ld_v2(mb + i * 256, x[2 * i], x[2 * i + 1]);
        TMARKD(mw == 0, 15, x[0]);
        TMARKD(mw == 0, 23, x[0] | x[2] | x[4] | x[6] | x[8] | x[10] | x[12] | x[14]);
        float c[4], e[4];
        mma16z(c, x[0], x[1], x[2], x[3], sel, sel);
        mma16z(e, x[4], x[5], x[6], x[7], sel, sel);
        mma16(c, x[8], x[9], x[10], x[11], sel, sel);
        mma16(e, x[12], x[13], x[14], x[15], sel, sel);
        const uint32_t bad = lop3<0xfe>(lop3<0x7e>(x[0], tagm, x[2]), lop3<0x7e>(x[4], tagm, x[6]), lop3<0x7e>(x[8], tagm, x[10])) | lop3<0x7e>(x[12], tagm, x[14]);
        const bool ok = !__any_sync(~0u, bad & 1u);
        const uint32_t w0 = pack2(c[0] + e[0], c[1] + e[1]), w1 = pack2(c[2] + e[2], c[3] + e[3]);
        const uint32_t wv = (ln & 1) ? w1 : w0;
        asm volatile("{.reg .pred p; setp.ne.u32 p, %2, 0; @p st.relaxed.gpu.global.u32 [%0], %1;}" ::"l"(pwp), "r"(wv), "r"((uint32_t)ok) : "memory");
        if (ok) { TMARKD(mw == 0, 9, wv); TMARKV(1, 24 + mw, it); break; }
        if (it > (1 << 16)) spend(budget = 0);
      }
      if (ln == 0) mbar_arrive(sb + B_PUB);
      st_u32(pwp + (32768 - 2 * (int)so), ~0u);
      if (D2) spin_clk_until(clk() + D2);
      sts32(sb + TK + mw * 4, min((gtime() - x1) / 32 + 1, 31u));
      if (s == 5 && ln == 0) st_u32(&g_tab[unit], 0u);
    }
    spin_gt_until(x2);
    TMARKD(mw == 0, 8, 0);
    for (int it = 0;; it++) {
      uint32_t x[4][4], m[4];
#pragma unroll
      for (int i = 0; i < 4; i++) ld_v4(pp + i * 512, x[i][0], x[i][1], x[i][2], x[i][3]);
#pragma unroll
      for (int i = 0; i < 4; i++) {
        sts128(ms + i * 512, x[i][0], x[i][1], x[i][2], x[i][3]);
        m[i] = max(max(x[i][0], x[i][1]), max(x[i][2], x[i][3]));
      }
      const bool ok = __all_sync(~0u, max(max(m[0], m[1]), max(m[2], m[3])) != ~0u);
      TMARKD(mw == 0 && ok, 10, 0); TMARKD(mw == 3 && ok, 11, 0);
      asm volatile("{.reg .pred p; setp.ne.u32 p, %0, 0; @p bar.sync 3, 384;}" ::"r"((uint32_t)ok) : "memory");
      if (ok) { TMARKV(1, 28 + mw, it); break; }
      if (it > (1 << 16)) spend(budget = 0);
    }
  }
}

__global__ void __cluster_dims__(3, 1, 1) __launch_bounds__(512, 1)
recur_kernel(const __grid_constant__ CUtensorMap tmX, const __grid_constant__ CUtensorMap tmWq,
             const __grid_constant__ CUtensorMap tmWk, const __grid_constant__ CUtensorMap tmWv,
             const bf16* __restrict__ mem0, const bf16* __restrict__ Wo) {
  using namespace rk;
  extern __shared__ unsigned char smem_raw[];
  const uint32_t sb = (smem_u32(smem_raw) + 1023u) & ~1023u;
  const int warp = __shfl_sync(~0u, threadIdx.x >> 5, 0), lane = threadIdx.x & 31;
  const uint32_t rank = blockIdx.x % 3u, head = blockIdx.x / 3u;
  int budget = 1 << 20;

  if (threadIdx.x == 0) {
    for (int i = 0; i < 4; i++) { mbar_init(sb + B_KV + 8 * i, 1); mbar_init(sb + B_W + 8 * i, 1); }
    mbar_init(sb + B_QKV, 9);
    for (int i = 0; i < 2; i++) mbar_init(sb + B_XF + 8 * i, 1);
    mbar_init(sb + B_FREE, 24);
    mbar_init(sb + B_OF, 4);
    mbar_init(sb + B_OE, 1);
    mbar_init(sb + B_PUB, 2);
    asm volatile("fence.mbarrier_init.release.cluster;" ::: "memory");
    mbar_arrive_tx(sb + B_QKV, 4096);
    const CUtensorMap* tw = rank == 0 ? &tmWq : rank == 1 ? &tmWk : &tmWv;
    for (int c = 0; c < 4; c++) {
      mbar_arrive_tx(sb + B_W + 8 * c, 32768);
      for (int i = 0; i < 4; i++) {
        const int kb = 2 * c + (i >> 1), nb = i & 1;
        tma_2d(sb + RA + (kb * 2 + nb) * 8192, tw, head * 128 + nb * 64, kb * 64, sb + B_W + 8 * c);
      }
    }
    for (int st = 0; st < 2; st++) {
      mbar_arrive_tx(sb + B_XF + 8 * st, 32768);
      tma_3d(sb + XT + st * 32768, &tmX, 0, st * 32, 0, sb + B_XF + 8 * st);
    }
  }
  cluster_sync_all();

  if (warp < 8) {
    asm volatile("setmaxnreg.inc.sync.aligned.u32 160;");
    if (lane == 0) sts32(sb + TK + 16 + warp * 4, near_page(g_pub + warp * 8192 + 2048 + blockIdx.x * 16));
    __syncwarp();
    bar_arrive(NB_TAB, 512);
    uint32_t w[112];
    const uint32_t wa = sb + RA + (warp >> 2) * 8192 + ((lane >> 4) * 8 + (lane & 7)) * 128 + (((2 * (warp & 3) + ((lane >> 3) & 1)) ^ (lane & 7)) << 4);
#pragma unroll
    for (int c = 0; c < 4; c++) {
      mbar_wait(sb + B_W + 8 * c, 0, budget);
#pragma unroll
      for (int jj = 0; jj < 8; jj++) {
        const int j = 8 * c + jj;
        if (j < 28) ldsm4t(wa + (j >> 2) * 16384 + (j & 3) * 2048, w[4 * j], w[4 * j + 1], w[4 * j + 2], w[4 * j + 3]);
      }
    }
    __syncwarp();
    asm volatile("griddepcontrol.launch_dependents;");
    if (lane < 3) mbar_arrive_remote(mapa(sb + B_FREE, lane));
    mbar_wait_cl(sb + B_FREE, 0, budget);
    for (int sg = 0; sg < 2; sg++) {
      float d[16];
      mbar_wait(sb + B_XF + 8 * sg, 0, budget);
      r_proj_issue(w, d, sb, sg, warp, 0, 32);
      wg_wait<0>();
      r_proj_store(d, sb, sg, warp, lane, rank);
      bar_sync(NB_P, 256);
      if (threadIdx.x == 0 && sg == 0) {
        r_proj_share(sb, 0, rank);
        mbar_arrive_tx(sb + B_XF, 32768);
        tma_3d(sb + XT, &tmX, 0, 64, 0, sb + B_XF);
      }
    }
    uint32_t ma = sb + MEMS + lane * 16;
    uint32_t dst0 = (rank == 0 ? QM : KV + (rank - 1) * 10240 + 8192) + 256 * warp + 4 * lane;
    OPAQUE(ma); OPAQUE(dst0);
    const uint32_t dstep = rank == 0 ? 0u : 20480u;
    for (int s = 0; s < kNSeg; s++) {
      float c0[4], c1[4];
      uint32_t wx[16], b[16][4];
#pragma unroll
      for (int j = 0; j < 4; j++) ldsm4t(wa + 7 * 16384 + j * 2048, wx[4 * j], wx[4 * j + 1], wx[4 * j + 2], wx[4 * j + 3]);
      const uint32_t dst = dst0 + (s & 3) * dstep;
      auto ldb = [&](int i) { ldsm4(ma + i * 512, b[i][0], b[i][1], b[i][2], b[i][3]); };
      bar_sync(NB_MEM, 384);
      ldb(14); ldb(15); ldb(0);
      TMARKD(warp == 0, 0, b[14][0]);
      mma16z(c0, wx[0], wx[1], wx[2], wx[3], b[14][0], b[14][1]);
      mma16z(c1, wx[4], wx[5], wx[6], wx[7], b[14][2], b[14][3]);
      ldb(1);
      mma16(c0, wx[8], wx[9], wx[10], wx[11], b[15][0], b[15][1]);
      mma16(c1, wx[12], wx[13], wx[14], wx[15], b[15][2], b[15][3]);
      ldb(2); ldb(3);
#pragma unroll
      for (int i = 0; i < 14; i++) {
        mma16(c0, w[8 * i], w[8 * i + 1], w[8 * i + 2], w[8 * i + 3], b[i][0], b[i][1]);
        mma16(c1, w[8 * i + 4], w[8 * i + 5], w[8 * i + 6], w[8 * i + 7], b[i][2], b[i][3]);
        if (i + 4 < 14) ldb(i + 4);
      }
      const uint32_t r0 = pack2(c0[0] + c1[0], c0[1] + c1[1]), r1 = pack2(c0[2] + c1[2], c0[3] + c1[3]);
#pragma unroll
      for (uint32_t d = 0; d < 2; d++) {
        const uint32_t base = mapa(sb, (rank + 1 + d) % 3u);
        st_async32(base + dst, r0, base + B_QKV);
        st_async32(base + dst + 128, r1, base + B_QKV);
      }
      sts32(sb + dst, r0);
      sts32(sb + dst + 128, r1);
      __syncwarp();
      if (lane == 0) mbar_arrive(sb + B_QKV);
      TMARKD(warp == 0, 1, r1);
      TMARKD(warp == 7, 12, r1);
      bar_sync(NB_P, 256);
      TMARKD(warp == 0, 14, 0);
      float d[16];
      if (s + 2 < kNSeg) mbar_wait(sb + B_XF + 8 * (s & 1), ((s + 2) >> 1) & 1, budget);
      r_proj_issue(w, d, sb, s, warp, 0, kSplit);
      if (warp == 0) {
        if (lane == 0) {
          if (s + 3 < kNSeg) {
            const uint32_t st = (s + 1) & 1;
            mbar_arrive_tx(sb + B_XF + 8 * st, 32768);
            tma_3d(sb + XT + st * 32768, &tmX, 0, (s + 3) * 32, 0, sb + B_XF + 8 * st);
          }
          mbar_wait(sb + B_QKV, s & 1, budget);
          if (s + 1 < kNSeg) r_proj_share(sb, s + 1, rank);
          if (rank == 0 && s > 1) {
            if (s > 2) r_flag_o(s - 3);
            r_store_o(sb, s - 2, head, budget);
          }
        }
        __syncwarp();
      }
      bar_sync(NB_TD, 384);
      TMARKD(warp == 1, 22, 0);
      if (rank == 0 && threadIdx.x == 0 && s > 1) {
        asm volatile("cp.async.bulk.wait_group.read 0;" ::: "memory");
        mbar_arrive(sb + B_OE);
      }
      __syncwarp();
      r_proj_issue(w, d, sb, s, warp, kSplit, kGate);
      if (rank != 0 && s + 1 < kNSeg) mbar_wait(sb + B_PUB, s & 1, budget);
      r_proj_issue(w, d, sb, s, warp, kGate, 32);
      wg_wait<0>();
      TMARKD(warp == 0, 7, __float_as_uint(d[0]));
      r_proj_store(d, sb, s + 2, warp, lane, rank);
      TMARKD(warp == 0, 2, 0);
    }
    if (rank == 0 && threadIdx.x == 0) {
      r_flag_o(kNSeg - 3);
      r_store_o(sb, kNSeg - 2, head, budget);
      asm volatile("cp.async.bulk.wait_group.read 0;" ::: "memory");
      mbar_arrive(sb + B_OE);
      r_flag_o(kNSeg - 2);
      r_store_o(sb, kNSeg - 1, head, budget);
      r_flag_o(kNSeg - 1);
    }
  } else if (warp < 12) {
    asm volatile("setmaxnreg.inc.sync.aligned.u32 136;");
    if (rank == 0) r_attn_role<2>(sb, warp - 8, lane, rank, head, Wo, budget);
    else r_attn_role<3>(sb, warp - 8, lane, rank, head, Wo, budget);
  } else {
    asm volatile("setmaxnreg.dec.sync.aligned.u32 56;");
    const int mw = warp - 12;
    const bool red = rank != 0 && mw < 2;
    const uint32_t unit = head * 4 + (rank - 1) * 2 + mw;
    const uint32_t pwo = (unit >> 5) * 8192 + (unit & 31) * 64;
    uint32_t mpage = 0;
    if (red) {
#pragma unroll
      for (int i = 0; i < 8; i++) st_b128(g_mail + unit * 8192 + (i >> 2) * 4096 + (i & 3) * 512 + lane * 16, 0u, 0u, 0u, 0u);
      st_v2(g_pub + pwo + (lane >> 4) * 32768 + ((lane >> 3) & 1) * 4096 + (lane & 7) * 8, ~0u, ~0u);
      if (lane == 0) mpage = near_page(g_mail + unit * 8192 + 2048);
      asm volatile("fence.acq_rel.gpu;" ::: "memory");
      mpage = __shfl_sync(~0u, mpage, 0);
      if (lane == 0) st_u32(&g_tab[unit], mpage | 1u);
    }
#pragma unroll
    for (int i = 0; i < 4; i++) {
      const int idx = mw * 128 + i * 32 + lane;
      const uint4 v = __ldg(reinterpret_cast<const uint4*>(mem0 + (idx & 7) * kD + (idx >> 3) * 8));
      sts128(sb + MEMS + idx * 16, v.x, v.y, v.z, v.w);
    }
    if (mw == 3 && lane < 2) sts32(sb + TK + lane * 4, 0u);
    {
      uint32_t v;
      while ((v = ld_u32(&g_tab[mw * 32 + lane])) == 0u) spend(budget);
      sts32(sb + TABS + (mw * 32 + lane) * 4, v);
      asm volatile("fence.acq_rel.gpu;" ::: "memory");
    }
    bar_sync(NB_TAB, 512);
    if (rank == 0) r_poll_role<false>(sb, mw, lane, unit);
    else r_poll_role<true>(sb, mw, lane, unit);
  }
  cluster_sync_all();
}

namespace gk {
constexpr int kCtas = 36, kStages = 4;
constexpr uint32_t STG = 49152;
constexpr uint32_t EPI = kStages * STG;
constexpr uint32_t BAR = EPI + 32768;
constexpr uint32_t INFO = BAR + 64;
constexpr uint32_t AUX = INFO + 16;
constexpr uint32_t SMEM = AUX + 64 + 1024;
constexpr int kF1 = 224, kF2 = 32;
constexpr int kFirstSplit = 9;
__host__ __device__ constexpr int nsplit(int rb) { return rb < 9 ? 1 : rb < 12 ? 2 : rb < 14 ? 4 : rb == 14 ? 8 : 16; }
constexpr int kWo = 2 * (9 + 6 + 8 + 8 + 16);
constexpr int kUnits = kF1 + kF2 + kWo;
constexpr uint32_t kDraws = kUnits + kCtas;
constexpr int NB_EPI = 1, NB_DEP = 2;
}

__device__ __forceinline__ void wgmma_256(float (&d)[128], uint64_t adesc, uint64_t bdesc, int acc) {
  asm volatile("{.reg .pred p; setp.ne.b32 p, %130, 0;\n"
    "wgmma.mma_async.sync.aligned.m64n256k16.f32.bf16.bf16 {"
    "%0,%1,%2,%3,%4,%5,%6,%7,%8,%9,%10,%11,%12,%13,%14,%15,%16,%17,%18,%19,%20,%21,%22,%23,%24,%25,%26,%27,%28,%29,%30,%31,"
    "%32,%33,%34,%35,%36,%37,%38,%39,%40,%41,%42,%43,%44,%45,%46,%47,%48,%49,%50,%51,%52,%53,%54,%55,%56,%57,%58,%59,%60,%61,%62,%63,"
    "%64,%65,%66,%67,%68,%69,%70,%71,%72,%73,%74,%75,%76,%77,%78,%79,%80,%81,%82,%83,%84,%85,%86,%87,%88,%89,%90,%91,%92,%93,%94,%95,"
    "%96,%97,%98,%99,%100,%101,%102,%103,%104,%105,%106,%107,%108,%109,%110,%111,%112,%113,%114,%115,%116,%117,%118,%119,%120,%121,%122,%123,%124,%125,%126,%127"
    "}, %128, %129, p, 1, 1, 0, 1;}"
#define D8(i) "+f"(d[i]), "+f"(d[i + 1]), "+f"(d[i + 2]), "+f"(d[i + 3]), "+f"(d[i + 4]), "+f"(d[i + 5]), "+f"(d[i + 6]), "+f"(d[i + 7])
    : D8(0), D8(8), D8(16), D8(24), D8(32), D8(40), D8(48), D8(56), D8(64), D8(72), D8(80), D8(88), D8(96), D8(104), D8(112), D8(120)
#undef D8
    : "l"(adesc), "l"(bdesc), "r"(acc));
}
__device__ __forceinline__ void bulk_g2s(uint32_t dst, const void* src, uint32_t bytes, uint32_t bar) {
  asm volatile("cp.async.bulk.shared::cluster.global.mbarrier::complete_tx::bytes [%0], [%1], %2, [%3];" ::"r"(dst), "l"(src), "r"(bytes), "r"(bar) : "memory");
}
__device__ __forceinline__ uint32_t ld_acq(const unsigned* p) { uint32_t v; asm volatile("ld.acquire.gpu.global.u32 %0, [%1];" : "=r"(v) : "l"(p) : "memory"); return v; }
__device__ __forceinline__ void wait_count(const unsigned* p, uint32_t target, int& budget) {
  while ((int)(ld_acq(p) - target) < 0) { spend(budget); __nanosleep(64); }
}
__device__ __forceinline__ float sigmoidf_(float x) { float t; asm("tanh.approx.f32 %0, %1;" : "=f"(t) : "f"(0.5f * x)); return fmaf(t, 0.5f, 0.5f); }
__device__ __forceinline__ uint32_t add_bf2(uint32_t a, uint32_t b) { uint32_t r; asm("add.rn.bf16x2 %0, %1, %2;" : "=r"(r) : "r"(a), "r"(b)); return r; }

template <bool ADD>
__device__ __forceinline__ void g_store_out(const float (&d)[128], float s0, float s1, uint32_t stg, bf16* __restrict__ dst, int lane) {
  const uint32_t wa = stg + (lane & 15) * 256, wx = (lane >> 4) ^ (lane & 7);
#pragma unroll
  for (int h = 0; h < 2; h++) {
    uint4 prev[8];
    if (ADD) {
#pragma unroll
      for (int i = 0; i < 8; i++) prev[i] = __ldcg(reinterpret_cast<const uint4*>(dst + (2 * i + (lane >> 4)) * kD + h * 128 + (lane & 15) * 8));
    }
#pragma unroll
    for (int i = 0; i < 8; i++) {
      const float* p = d + 64 * h + 8 * i;
      stsm4(wa + (((2 * i) ^ wx) << 4), pack2(p[0] * s0, p[1] * s0), pack2(p[2] * s1, p[3] * s1), pack2(p[4] * s0, p[5] * s0), pack2(p[6] * s1, p[7] * s1));
    }
    __syncwarp();
#pragma unroll
    for (int i = 0; i < 8; i++) {
      const int row = 2 * i + (lane >> 4);
      uint4 v;
      lds128(stg + row * 256 + (((lane & 15) ^ (row & 7)) << 4), v.x, v.y, v.z, v.w);
      if (ADD) { v.x = add_bf2(v.x, prev[i].x); v.y = add_bf2(v.y, prev[i].y); v.z = add_bf2(v.z, prev[i].z); v.w = add_bf2(v.w, prev[i].w); }
      *reinterpret_cast<uint4*>(dst + row * kD + h * 128 + (lane & 15) * 8) = v;
    }
    __syncwarp();
  }
}

__global__ void __launch_bounds__(384, 1)
gemm_kernel(const __grid_constant__ CUtensorMap tmX, const __grid_constant__ CUtensorMap tmWg, const __grid_constant__ CUtensorMap tmWu,
            const __grid_constant__ CUtensorMap tmWd, const __grid_constant__ CUtensorMap tmWo,
            const bf16* __restrict__ x, const bf16* __restrict__ gw, bf16* __restrict__ out) {
  using namespace gk;
  extern __shared__ unsigned char smem_raw[];
  const uint32_t sb = (smem_u32(smem_raw) + 1023u) & ~1023u;
  const int warp = __shfl_sync(~0u, threadIdx.x >> 5, 0), lane = threadIdx.x & 31;
  int budget = 1 << 20;
  if (threadIdx.x == 0) {
    for (int i = 0; i < kStages; i++) { mbar_init(sb + BAR + 8 * i, 1); mbar_init(sb + BAR + 32 + 8 * i, 2); }
    asm volatile("fence.mbarrier_init.release.cluster;" ::: "memory");
  }
  __syncthreads();

  if (warp < 4) {
    asm volatile("setmaxnreg.dec.sync.aligned.u32 40;");
    if (warp == 0) {
      if (lane == 0) {
        uint32_t it = 0;
        while (true) {
          const uint32_t tk = atomicAdd(&g_ticket, 1u);
          const uint32_t ep = tk / kDraws + 1;
          int u = tk % kDraws, type, rb, nb, piece = 0, k0 = 0, nk;
          if (u < kF1) { type = 0; rb = u / 14; nb = u % 14; nk = 8; }
          else if (u < kF1 + kF2) { type = 1; rb = (u - kF1) >> 1; nb = u & 1; nk = 28; }
          else if (u < kUnits) {
            type = 2; u -= kF1 + kF2; rb = 0;
            while (u >= 2 * nsplit(rb)) { u -= 2 * nsplit(rb); rb++; }
            nb = u & 1; piece = u >> 1; nk = 64 / nsplit(rb); k0 = piece * nk;
          } else { type = 3; rb = nb = 0; nk = 1; }
          const uint32_t code = type | rb << 2 | nb << 6 | piece << 10 | ep << 14;
          const bf16* asrc = type == 1 ? g_hid + (size_t)rb * 28 * 8192 : g_o + (size_t)(rb * 64 + k0) * 8192;
          const int pre = type == 0 ? 0 : nk < kStages ? nk : kStages;
          for (int k = 0; k < nk; k++) {
            const uint32_t st = (it + k) % kStages, ph = ((it + k) / kStages) & 1;
            const uint32_t full = sb + BAR + 8 * st, sa = sb + st * STG;
            mbar_wait(full + 32, ph ^ 1, budget);
            asm volatile("st.shared.u32 [%0], %1;" ::"r"(sb + INFO + 4 * st), "r"(code) : "memory");
            if (type == 3) { mbar_arrive(full); break; }
            mbar_arrive_tx(full, STG);
            if (type == 0) {
              tma_2d(sa, &tmX, k * 64, rb * 128, full);
              tma_3d(sa + 16384, &tmWg, 0, k * 64, nb * 2, full);
              tma_3d(sa + 32768, &tmWu, 0, k * 64, nb * 2, full);
            } else {
              tma_3d(sa + 16384, type == 1 ? &tmWd : &tmWo, 0, (k0 + k) * 64, nb * 4, full);
              if (k >= pre) bulk_g2s(sa, asrc + k * 8192, 16384, full);
              else if (k == pre - 1) {
                if (type == 1) wait_count(&g_cnt[C_HID + rb], ep * 16, budget);
                else wait_count(&g_cnt[C_O + rb], ep * 128, budget);
                asm volatile("fence.proxy.async.global;" ::: "memory");
                for (int j = 0; j < pre; j++) bulk_g2s(sb + ((it + j) % kStages) * STG, asrc + j * 8192, 16384, sb + BAR + 8 * ((it + j) % kStages));
              }
            }
          }
          if (type == 3) break;
          it += nk;
        }
      }
    } else if (warp == 1) {
      while (true) {
        bar_sync(NB_EPI, 288);
        uint32_t idx;
        asm volatile("ld.shared.u32 %0, [%1];" : "=r"(idx) : "r"(sb + AUX) : "memory");
        bar_arrive(NB_DEP, 288);
        if (idx == ~0u) break;
        if (lane == 0) asm volatile("fence.proxy.async.global; red.release.gpu.global.add.u32 [%0], 1;" ::"l"(&g_cnt[idx]) : "memory");
      }
    } else if (blockIdx.x < 16) {
      float w[16];
#pragma unroll
      for (int i = 0; i < 2; i++) {
        const uint4 v = __ldg(reinterpret_cast<const uint4*>(gw + i * 256 + lane * 8));
        const uint32_t q[4] = {v.x, v.y, v.z, v.w};
#pragma unroll
        for (int j = 0; j < 4; j++) { w[8 * i + 2 * j] = __uint_as_float(q[j] << 16); w[8 * i + 2 * j + 1] = __uint_as_float(q[j] & 0xffff0000u); }
      }
      const int r0 = blockIdx.x * 128 + (warp - 2) * 64;
      for (int r = r0; r < r0 + 64; r++) {
        float a = 0.f;
#pragma unroll
        for (int i = 0; i < 2; i++) {
          const uint4 v = __ldg(reinterpret_cast<const uint4*>(x + r * kD + i * 256 + lane * 8));
          const uint32_t q[4] = {v.x, v.y, v.z, v.w};
#pragma unroll
          for (int j = 0; j < 4; j++) a = fmaf(__uint_as_float(q[j] << 16), w[8 * i + 2 * j], fmaf(__uint_as_float(q[j] & 0xffff0000u), w[8 * i + 2 * j + 1], a));
        }
#pragma unroll
        for (int o = 16; o; o >>= 1) a += __shfl_xor_sync(~0u, a, o);
        if (lane == 0) g_gate[r] = 1.f / (1.f + __expf(-a));
      }
      if (lane == 0) asm volatile("red.release.gpu.global.add.u32 [%0], 1;" ::"l"(&g_cnt[C_HID + blockIdx.x]) : "memory");
    }
  } else {
    asm volatile("setmaxnreg.inc.sync.aligned.u32 232;");
    const int cw = warp - 4, ct = threadIdx.x - 128;
    const uint32_t stg = sb + EPI + cw * 4096;
    uint32_t it = 0;
    bool pending = false;
    float d[128];
    while (true) {
      mbar_wait(sb + BAR + 8 * (it % kStages), (it / kStages) & 1, budget);
      uint32_t code;
      asm volatile("ld.shared.u32 %0, [%1];" : "=r"(code) : "r"(sb + INFO + 4 * (it % kStages)) : "memory");
      const int type = code & 3, rb = (code >> 2) & 15, nb = (code >> 6) & 15;
      const uint32_t ep = code >> 14;
      if (type == 3) break;
      const int nk = type == 0 ? 8 : type == 1 ? 28 : 64 / nsplit(rb);
      for (int k = 0; k < nk; k++, it++) {
        const uint32_t st = it % kStages;
        if (k) mbar_wait(sb + BAR + 8 * st, (it / kStages) & 1, budget);
        const uint64_t ad = make_desc(sb + st * STG + (cw >> 2) * 8192, 16, 1024, 1);
        const uint64_t bd = make_desc(sb + st * STG + 16384, 8192, 1024, 1);
        wg_fence();
#pragma unroll
        for (int j = 0; j < 4; j++) wgmma_256(d, ad + (uint64_t)(2 * j), bd + (uint64_t)(128 * j), k | j);
        wg_commit();
        wg_wait<1>();
        if (k && (ct & 127) == 0) mbar_arrive(sb + BAR + 32 + 8 * ((it - 1) % kStages));
      }
      wg_wait<0>();
      if ((ct & 127) == 0) mbar_arrive(sb + BAR + 32 + 8 * ((it - 1) % kStages));
      const int row = rb * 128 + cw * 16;
      uint32_t flag = ~1u;
      if (type == 0) {
        const uint32_t wa = stg + (lane & 15) * 128, wx = (lane >> 4) ^ (lane & 7);
#pragma unroll
        for (int i = 0; i < 8; i++) {
          float h[8];
#pragma unroll
          for (int j = 0; j < 8; j++) h[j] = sigmoidf_(d[8 * i + j]) * d[64 + 8 * i + j];
          stsm4(wa + (i >> 2) * 2048 + (((2 * (i & 3)) ^ wx) << 4), pack2(h[0], h[1]), pack2(h[2], h[3]), pack2(h[4], h[5]), pack2(h[6], h[7]));
        }
        __syncwarp();
        bf16* dst = g_hid + (size_t)(rb * 28 + nb * 2) * 8192 + cw * 1024 + lane * 8;
#pragma unroll
        for (int i = 0; i < 8; i++) {
          uint4 v;
          lds128(stg + i * 512 + lane * 16, v.x, v.y, v.z, v.w);
          *reinterpret_cast<uint4*>(dst + (i >> 2) * 8192 + (i & 3) * 256) = v;
        }
        __syncwarp();
        flag = C_HID + rb;
      } else {
        const int tile = rb * 2 + nb;
        float4* acc = reinterpret_cast<float4*>(g_acc) + (size_t)(tile - 2 * kFirstSplit) * 8192 + ct;
        bf16* dst = out + row * kD + nb * 256;
        if (type == 2) {
          if (lane == 0) wait_count(&g_cnt[C_F2 + tile], ep, budget);
          __syncwarp();
        }
        const float g0 = __ldcg(&g_gate[row + (lane >> 2)]), g1 = __ldcg(&g_gate[row + 8 + (lane >> 2)]);
        if (type == 1) {
          const float s0 = 1.f - g0, s1 = 1.f - g1;
          if (rb < kFirstSplit) g_store_out<false>(d, s0, s1, stg, dst, lane);
          else {
#pragma unroll
            for (int i = 0; i < 32; i++) acc[i * 256] = make_float4(d[4 * i] * s0, d[4 * i + 1] * s0, d[4 * i + 2] * s1, d[4 * i + 3] * s1);
          }
          flag = C_F2 + tile;
        } else if (rb < kFirstSplit) {
          g_store_out<true>(d, g0, g1, stg, dst, lane);
        } else {
          const uint32_t ns = nsplit(rb);
          uint32_t tk = 0;
          if (lane == 0) tk = atomicAdd(&g_cnt[C_ARR + tile * 8 + cw], 1u);
          tk = __shfl_sync(~0u, tk, 0);
          if (tk != ep * ns - 1) {
#pragma unroll
            for (int i = 0; i < 32; i++)
              asm volatile("red.relaxed.gpu.global.add.v4.f32 [%0], {%1,%2,%3,%4};" ::"l"(acc + i * 256), "f"(d[4 * i] * g0), "f"(d[4 * i + 1] * g0),
                           "f"(d[4 * i + 2] * g1), "f"(d[4 * i + 3] * g1) : "memory");
            __syncwarp();
            if (lane == 0) asm volatile("red.release.gpu.global.add.u32 [%0], 1;" ::"l"(&g_cnt[C_DONE + tile * 8 + cw]) : "memory");
          } else {
            if (lane == 0) wait_count(&g_cnt[C_DONE + tile * 8 + cw], ep * (ns - 1), budget);
            __syncwarp();
#pragma unroll
            for (int i = 0; i < 32; i++) {
              const float4 v = __ldcg(acc + i * 256);
              d[4 * i] = fmaf(d[4 * i], g0, v.x); d[4 * i + 1] = fmaf(d[4 * i + 1], g0, v.y);
              d[4 * i + 2] = fmaf(d[4 * i + 2], g1, v.z); d[4 * i + 3] = fmaf(d[4 * i + 3], g1, v.w);
            }
            g_store_out<false>(d, 1.f, 1.f, stg, dst, lane);
          }
        }
      }
      if (flag != ~1u) {
        if (pending) bar_sync(NB_DEP, 288);
        if (ct == 0) asm volatile("st.shared.u32 [%0], %1;" ::"r"(sb + AUX), "r"(flag) : "memory");
        bar_arrive(NB_EPI, 288);
        pending = true;
      }
    }
    if (pending) bar_sync(NB_DEP, 288);
    if (ct == 0) asm volatile("st.shared.u32 [%0], %1;" ::"r"(sb + AUX), "r"(~0u) : "memory");
    bar_arrive(NB_EPI, 288);
    bar_sync(NB_DEP, 288);
  }
}

typedef CUresult (*EncodeFn)(CUtensorMap*, CUtensorMapDataType, cuuint32_t, void*, const cuuint64_t*, const cuuint64_t*,
                             const cuuint32_t*, const cuuint32_t*, CUtensorMapInterleave, CUtensorMapSwizzle,
                             CUtensorMapL2promotion, CUtensorMapFloatOOBfill);

static void make_map(EncodeFn fn, CUtensorMap* m, const void* base, uint64_t cols, uint64_t rows, uint32_t bc, uint32_t br) {
  cuuint64_t dims[2] = {cols, rows};
  cuuint64_t strides[1] = {cols * 2};
  cuuint32_t box[2] = {bc, br};
  cuuint32_t es[2] = {1, 1};
  fn(m, CU_TENSOR_MAP_DATA_TYPE_BFLOAT16, 2, const_cast<void*>(base), dims, strides, box, es, CU_TENSOR_MAP_INTERLEAVE_NONE,
     CU_TENSOR_MAP_SWIZZLE_128B, CU_TENSOR_MAP_L2_PROMOTION_L2_256B, CU_TENSOR_MAP_FLOAT_OOB_FILL_NONE);
}

static void make_map3(EncodeFn fn, CUtensorMap* m, const void* base, uint64_t cols, uint64_t rows, uint32_t br, uint32_t nc) {
  cuuint64_t dims[3] = {64, rows, cols / 64};
  cuuint64_t strides[2] = {cols * 2, 128};
  cuuint32_t box[3] = {64, br, nc};
  cuuint32_t es[3] = {1, 1, 1};
  fn(m, CU_TENSOR_MAP_DATA_TYPE_BFLOAT16, 3, const_cast<void*>(base), dims, strides, box, es, CU_TENSOR_MAP_INTERLEAVE_NONE,
     CU_TENSOR_MAP_SWIZZLE_128B, CU_TENSOR_MAP_L2_PROMOTION_L2_256B, CU_TENSOR_MAP_FLOAT_OOB_FILL_NONE);
}

extern "C" void kernel_launch(void* const* d_in, const int* in_sizes, int n_in, void* d_out, int out_size) {
  const bf16* x = (const bf16*)d_in[0];
  const bf16* mem0 = (const bf16*)d_in[1];
  const bf16* Wo = (const bf16*)d_in[5];
  void* fp = nullptr;
  cudaDriverEntryPointQueryResult qr;
  cudaGetDriverEntryPoint("cuTensorMapEncodeTiled", &fp, cudaEnableDefault, &qr);
  EncodeFn fn = (EncodeFn)fp;
  CUtensorMap tmX, tmWq, tmWk, tmWv;
  make_map3(fn, &tmX, x, kD, kS, 32, 8);
  make_map(fn, &tmWq, d_in[2], 4096, kD, 64, 64);
  make_map(fn, &tmWk, d_in[3], 4096, kD, 64, 64);
  make_map(fn, &tmWv, d_in[4], 4096, kD, 64, 64);
  cudaFuncSetAttribute(recur_kernel, cudaFuncAttributeMaxDynamicSharedMemorySize, rk::SMEM);
  recur_kernel<<<96, 512, rk::SMEM>>>(tmX, tmWq, tmWk, tmWv, mem0, Wo);
  CUtensorMap tmX2, tmWg, tmWu, tmWd, tmWo;
  make_map(fn, &tmX2, x, kD, kS, 64, 128);
  make_map3(fn, &tmWg, d_in[8], kF, kD, 64, 2);
  make_map3(fn, &tmWu, d_in[9], kF, kD, 64, 2);
  make_map3(fn, &tmWd, d_in[10], kD, kF, 64, 4);
  make_map3(fn, &tmWo, Wo, kD, 4096, 64, 4);
  cudaFuncSetAttribute(gemm_kernel, cudaFuncAttributeMaxDynamicSharedMemorySize, gk::SMEM);
  cudaLaunchConfig_t cfg = {};
  cfg.gridDim = dim3(gk::kCtas);
  cfg.blockDim = dim3(384);
  cfg.dynamicSmemBytes = gk::SMEM;
  cfg.stream = cudaStreamPerThread;
  cudaLaunchAttribute at[1];
  at[0].id = cudaLaunchAttributeProgrammaticStreamSerialization;
  at[0].val.programmaticStreamSerializationAllowed = 1;
  cfg.attrs = at;
  cfg.numAttrs = 1;
  cudaLaunchKernelEx(&cfg, gemm_kernel, tmX2, tmWg, tmWu, tmWd, tmWo, x, (const bf16*)d_in[11], (bf16*)d_out);
}
```

```cpp
#include <cuda_runtime.h>
#include <cuda_bf16.h>
#include <cuda.h>
#include <stdint.h>

typedef __nv_bfloat16 bf16;

constexpr int kS = 2048, kD = 512, kH = 32, kF = 1792, kNSeg = 64;

__device__ __align__(8192) unsigned char g_mail[128 * 8192];
__device__ __align__(8192) unsigned char g_pub[65536];
__device__ __align__(16) unsigned g_tab[128];
__device__ __align__(1024) bf16 g_o[(size_t)kS * 4096];
__device__ __align__(1024) bf16 g_q[(size_t)kS * 4096];
__device__ __align__(1024) bf16 g_hid[kS * kF];
__device__ __align__(16) float g_acc[14 * 128 * 256];
__device__ float g_gate[kS];
__device__ unsigned g_ticket;
constexpr int C_HID = 0, C_O = 16, C_F2 = 32, C_ARR = 64, C_DONE = 320, C_Q = 576;
__device__ unsigned g_cnt[832];

#define TMARKD(cond, ev, dep)
#define TMARKV(cond, ev, v)
#define TSTAMP(cond, i)
#define TMARKW(set, ev, dep)
#define OPAQUE(v_) v_ = __shfl_xor_sync(~0u, v_, 0)

__device__ __forceinline__ uint32_t smem_u32(const void* p) { return (uint32_t)__cvta_generic_to_shared(p); }
__device__ __forceinline__ void mbar_init(uint32_t a, uint32_t n) { asm volatile("mbarrier.init.shared::cta.b64 [%0], %1;" ::"r"(a), "r"(n) : "memory"); }
__device__ __forceinline__ void mbar_arrive(uint32_t a) { asm volatile("mbarrier.arrive.shared::cta.b64 _, [%0];" ::"r"(a) : "memory"); }
__device__ __forceinline__ void mbar_arrive_tx(uint32_t a, uint32_t b) { asm volatile("mbarrier.arrive.expect_tx.shared::cta.b64 _, [%0], %1;" ::"r"(a), "r"(b) : "memory"); }
__device__ __forceinline__ void mbar_arrive_remote(uint32_t a) { asm volatile("mbarrier.arrive.release.cluster.shared::cluster.b64 _, [%0];" ::"r"(a) : "memory"); }
__device__ __forceinline__ bool mbar_try(uint32_t a, uint32_t par) {
  uint32_t ok;
  asm volatile("{.reg .pred p; mbarrier.try_wait.parity.shared::cta.b64 p, [%1], %2; selp.u32 %0, 1, 0, p;}" : "=r"(ok) : "r"(a), "r"(par) : "memory");
  return ok;
}
__device__ __forceinline__ bool mbar_try_cl(uint32_t a, uint32_t par) {
  uint32_t ok;
  asm volatile("{.reg .pred p; mbarrier.try_wait.parity.acquire.cluster.shared::cta.b64 p, [%1], %2; selp.u32 %0, 1, 0, p;}" : "=r"(ok) : "r"(a), "r"(par) : "memory");
  return ok;
}
__device__ __forceinline__ void spend(int& budget) { asm volatile("{.reg .pred p; .reg .u64 z; mov.u64 z, 0; add.s32 %0, %0, -1; setp.lt.s32 p, %0, 0; @p st.global.u32 [z], %0;}" : "+r"(budget)); }
__device__ __forceinline__ void mbar_wait(uint32_t a, uint32_t par, int& budget) { while (!mbar_try(a, par)) { spend(budget); } }
__device__ __forceinline__ void mbar_wait(uint32_t a, uint32_t par) {
  if (!mbar_try(a, par)) { int budget = 1 << 18; do { spend(budget); } while (!mbar_try(a, par)); }
}
__device__ __forceinline__ void mbar_wait_cl(uint32_t a, uint32_t par) { int budget = 1 << 18; while (!mbar_try_cl(a, par)) { spend(budget); } }
__device__ __forceinline__ uint32_t mapa(uint32_t a, uint32_t r) { uint32_t o; asm("mapa.shared::cluster.u32 %0, %1, %2;" : "=r"(o) : "r"(a), "r"(r)); return o; }
__device__ __forceinline__ void fence_async_smem() { asm volatile("fence.proxy.async.shared::cta;" ::: "memory"); }
__device__ __forceinline__ void bar_sync(int id, int n) { asm volatile("bar.sync %0, %1;" ::"r"(id), "r"(n) : "memory"); }
__device__ __forceinline__ void bar_sync_after(int id, int n, uint32_t dep, uint32_t skip) {
  asm volatile("{.reg .pred p; setp.eq.u32 p, %2, 0; @p bar.sync %0, %1;}" ::"r"(id), "r"(n), "r"((dep & blockIdx.y) | skip) : "memory");
}
__device__ __forceinline__ bool bar_red_or(int id, int n, bool v) {
  uint32_t r;
  asm volatile("{.reg .pred p, q; setp.ne.u32 q, %3, 0; bar.red.or.pred p, %1, %2, q; selp.u32 %0, 1, 0, p;}" : "=r"(r) : "r"(id), "r"(n), "r"((uint32_t)v) : "memory");
  return r;
}
__device__ __forceinline__ void bar_arrive(int id, int n) { asm volatile("bar.arrive %0, %1;" ::"r"(id), "r"(n) : "memory"); }
__device__ __forceinline__ void cluster_sync_all() {
  asm volatile("barrier.cluster.arrive.release.aligned; barrier.cluster.wait.acquire.aligned;" ::: "memory");
}
__device__ __forceinline__ void tma_2d(uint32_t dst, const CUtensorMap* tm, int c0, int c1, uint32_t bar) {
  asm volatile("cp.async.bulk.tensor.2d.shared::cluster.global.mbarrier::complete_tx::bytes [%0], [%1, {%3, %4}], [%2];"
               ::"r"(dst), "l"(tm), "r"(bar), "r"(c0), "r"(c1) : "memory");
}
__device__ __forceinline__ void tma_3d(uint32_t dst, const CUtensorMap* tm, int c0, int c1, int c2, uint32_t bar) {
  asm volatile("cp.async.bulk.tensor.3d.shared::cluster.global.mbarrier::complete_tx::bytes [%0], [%1, {%3, %4, %5}], [%2];"
               ::"r"(dst), "l"(tm), "r"(bar), "r"(c0), "r"(c1), "r"(c2) : "memory");
}
__device__ __forceinline__ void bulk_s2c(uint32_t dst, uint32_t src, uint32_t bytes, uint32_t bar) {
  asm volatile("cp.async.bulk.shared::cluster.shared::cta.mbarrier::complete_tx::bytes [%0], [%1], %2, [%3];"
               ::"r"(dst), "r"(src), "r"(bytes), "r"(bar) : "memory");
}
__device__ __forceinline__ void bulk_g2s(uint32_t dst, const void* src, uint32_t bytes, uint32_t bar) {
  asm volatile("cp.async.bulk.shared::cluster.global.mbarrier::complete_tx::bytes [%0], [%1], %2, [%3];" ::"r"(dst), "l"(src), "r"(bytes), "r"(bar) : "memory");
}
__device__ __forceinline__ void bulk_s2g(void* dst, uint32_t src, uint32_t bytes) {
  asm volatile("cp.async.bulk.global.shared::cta.bulk_group [%0], [%1], %2;" ::"l"(dst), "r"(src), "r"(bytes) : "memory");
}
__device__ __forceinline__ void st_async32(uint32_t dst, uint32_t v, uint32_t bar) {
  asm volatile("st.async.weak.shared::cluster.mbarrier::complete_tx::bytes.b32 [%0], %1, [%2];" ::"r"(dst), "r"(v), "r"(bar) : "memory");
}
__device__ __forceinline__ void ldsm4(uint32_t a, uint32_t& r0, uint32_t& r1, uint32_t& r2, uint32_t& r3) {
  asm volatile("ldmatrix.sync.aligned.m8n8.x4.shared.b16 {%0,%1,%2,%3}, [%4];" : "=r"(r0), "=r"(r1), "=r"(r2), "=r"(r3) : "r"(a) : "memory");
}
__device__ __forceinline__ void ldsm4t(uint32_t a, uint32_t& r0, uint32_t& r1, uint32_t& r2, uint32_t& r3) {
  asm volatile("ldmatrix.sync.aligned.m8n8.x4.trans.shared.b16 {%0,%1,%2,%3}, [%4];" : "=r"(r0), "=r"(r1), "=r"(r2), "=r"(r3) : "r"(a) : "memory");
}
__device__ __forceinline__ void ldsm2t(uint32_t a, uint32_t& r0, uint32_t& r1) {
  asm volatile("ldmatrix.sync.aligned.m8n8.x2.trans.shared.b16 {%0,%1}, [%2];" : "=r"(r0), "=r"(r1) : "r"(a) : "memory");
}
__device__ __forceinline__ void stsm4(uint32_t a, uint32_t r0, uint32_t r1, uint32_t r2, uint32_t r3) {
  asm volatile("stmatrix.sync.aligned.m8n8.x4.shared.b16 [%0], {%1,%2,%3,%4};" ::"r"(a), "r"(r0), "r"(r1), "r"(r2), "r"(r3) : "memory");
}
__device__ __forceinline__ void stsm2(uint32_t a, uint32_t r0, uint32_t r1) {
  asm volatile("stmatrix.sync.aligned.m8n8.x2.shared.b16 [%0], {%1,%2};" ::"r"(a), "r"(r0), "r"(r1) : "memory");
}
__device__ __forceinline__ void stsm4t(uint32_t a, uint32_t r0, uint32_t r1, uint32_t r2, uint32_t r3) {
  asm volatile("stmatrix.sync.aligned.m8n8.x4.trans.shared.b16 [%0], {%1,%2,%3,%4};" ::"r"(a), "r"(r0), "r"(r1), "r"(r2), "r"(r3) : "memory");
}
__device__ __forceinline__ void stsm1t(uint32_t a, uint32_t r0) {
  asm volatile("stmatrix.sync.aligned.m8n8.x1.trans.shared.b16 [%0], {%1};" ::"r"(a), "r"(r0) : "memory");
}
__device__ __forceinline__ void mma16z(float (&c)[4], uint32_t a0, uint32_t a1, uint32_t a2, uint32_t a3, uint32_t b0, uint32_t b1) {
  asm volatile("mma.sync.aligned.m16n8k16.row.col.f32.bf16.bf16.f32 {%0,%1,%2,%3}, {%4,%5,%6,%7}, {%8,%9}, {%10,%10,%10,%10};"
               : "=f"(c[0]), "=f"(c[1]), "=f"(c[2]), "=f"(c[3]) : "r"(a0), "r"(a1), "r"(a2), "r"(a3), "r"(b0), "r"(b1), "f"(0.f));
}
__device__ __forceinline__ void mma16(float (&c)[4], uint32_t a0, uint32_t a1, uint32_t a2, uint32_t a3, uint32_t b0, uint32_t b1) {
  asm volatile("mma.sync.aligned.m16n8k16.row.col.f32.bf16.bf16.f32 {%0,%1,%2,%3}, {%4,%5,%6,%7}, {%8,%9}, {%0,%1,%2,%3};"
               : "+f"(c[0]), "+f"(c[1]), "+f"(c[2]), "+f"(c[3]) : "r"(a0), "r"(a1), "r"(a2), "r"(a3), "r"(b0), "r"(b1));
}
__device__ __forceinline__ void mma8(float (&c)[4], uint32_t a0, uint32_t a1, uint32_t b0) {
  asm volatile("mma.sync.aligned.m16n8k8.row.col.f32.bf16.bf16.f32 {%0,%1,%2,%3}, {%4,%5}, {%6}, {%0,%1,%2,%3};"
               : "+f"(c[0]), "+f"(c[1]), "+f"(c[2]), "+f"(c[3]) : "r"(a0), "r"(a1), "r"(b0));
}
__device__ __forceinline__ void mma8z(float (&c)[4], uint32_t a0, uint32_t a1, uint32_t b0) {
  asm volatile("mma.sync.aligned.m16n8k8.row.col.f32.bf16.bf16.f32 {%0,%1,%2,%3}, {%4,%5}, {%6}, {%7,%7,%7,%7};"
               : "=f"(c[0]), "=f"(c[1]), "=f"(c[2]), "=f"(c[3]) : "r"(a0), "r"(a1), "r"(b0), "f"(0.f));
}
__device__ __forceinline__ uint32_t pack2(float lo, float hi) {
  uint32_t r; asm("cvt.rn.bf16x2.f32 %0, %1, %2;" : "=r"(r) : "f"(hi), "f"(lo)); return r;
}
__device__ __forceinline__ float ex2(float x) { float r; asm("ex2.approx.ftz.f32 %0, %1;" : "=f"(r) : "f"(x)); return r; }
__device__ __forceinline__ void wg_fence() { asm volatile("wgmma.fence.sync.aligned;" ::: "memory"); }
__device__ __forceinline__ void wg_commit() { asm volatile("wgmma.commit_group.sync.aligned;" ::: "memory"); }
template <int N> __device__ __forceinline__ void wg_wait() { asm volatile("wgmma.wait_group.sync.aligned %0;" ::"n"(N) : "memory"); }
template <int TB>
__device__ __forceinline__ void wgmma_rs32(float (&d)[16], uint32_t a0, uint32_t a1, uint32_t a2, uint32_t a3, uint64_t desc, int acc) {
  asm volatile("{.reg .pred p; setp.ne.b32 p, %21, 0;\n"
               "wgmma.mma_async.sync.aligned.m64n32k16.f32.bf16.bf16 {%0,%1,%2,%3,%4,%5,%6,%7,%8,%9,%10,%11,%12,%13,%14,%15}, {%16,%17,%18,%19}, %20, p, 1, 1, %22;}"
               : "+f"(d[0]), "+f"(d[1]), "+f"(d[2]), "+f"(d[3]), "+f"(d[4]), "+f"(d[5]), "+f"(d[6]), "+f"(d[7]),
                 "+f"(d[8]), "+f"(d[9]), "+f"(d[10]), "+f"(d[11]), "+f"(d[12]), "+f"(d[13]), "+f"(d[14]), "+f"(d[15])
               : "r"(a0), "r"(a1), "r"(a2), "r"(a3), "l"(desc), "r"(acc), "n"(TB));
}
template <int TA, int TB>
__device__ __forceinline__ void wgmma_ss32(float (&d)[16], uint64_t adesc, uint64_t desc, int acc) {
  asm volatile("{.reg .pred p; setp.ne.b32 p, %18, 0;\n"
               "wgmma.mma_async.sync.aligned.m64n32k16.f32.bf16.bf16 {%0,%1,%2,%3,%4,%5,%6,%7,%8,%9,%10,%11,%12,%13,%14,%15}, %16, %17, p, 1, 1, %19, %20;}"
               : "+f"(d[0]), "+f"(d[1]), "+f"(d[2]), "+f"(d[3]), "+f"(d[4]), "+f"(d[5]), "+f"(d[6]), "+f"(d[7]),
                 "+f"(d[8]), "+f"(d[9]), "+f"(d[10]), "+f"(d[11]), "+f"(d[12]), "+f"(d[13]), "+f"(d[14]), "+f"(d[15])
               : "l"(adesc), "l"(desc), "r"(acc), "n"(TA), "n"(TB));
}
__device__ __forceinline__ void wgmma_ss40(float (&d)[20], uint64_t adesc, uint64_t desc, int acc) {
  asm volatile("{.reg .pred p; setp.ne.b32 p, %22, 0;\n"
               "wgmma.mma_async.sync.aligned.m64n40k16.f32.bf16.bf16 {%0,%1,%2,%3,%4,%5,%6,%7,%8,%9,%10,%11,%12,%13,%14,%15,%16,%17,%18,%19}, %20, %21, p, 1, 1, 0, 1;}"
               : "+f"(d[0]), "+f"(d[1]), "+f"(d[2]), "+f"(d[3]), "+f"(d[4]), "+f"(d[5]), "+f"(d[6]), "+f"(d[7]),
                 "+f"(d[8]), "+f"(d[9]), "+f"(d[10]), "+f"(d[11]), "+f"(d[12]), "+f"(d[13]), "+f"(d[14]), "+f"(d[15]),
                 "+f"(d[16]), "+f"(d[17]), "+f"(d[18]), "+f"(d[19])
               : "l"(adesc), "l"(desc), "r"(acc));
}
__device__ __forceinline__ float rcp(float x) { float r; asm("rcp.approx.ftz.f32 %0, %1;" : "=f"(r) : "f"(x)); return r; }
__device__ __forceinline__ uint64_t make_desc(uint32_t addr, uint32_t lbo, uint32_t sbo, uint32_t swz) {
  return (uint64_t)((addr & 0x3FFFF) >> 4) | ((uint64_t)(lbo >> 4) << 16) | ((uint64_t)(sbo >> 4) << 32) | ((uint64_t)swz << 62);
}
__device__ __forceinline__ void ld_b128(const void* p, uint32_t& a, uint32_t& b, uint32_t& c, uint32_t& d) {
  asm volatile("{.reg .b128 t; .reg .b64 lo, hi; ld.relaxed.gpu.global.b128 t, [%4]; mov.b128 {lo, hi}, t; mov.b64 {%0,%1}, lo; mov.b64 {%2,%3}, hi;}"
               : "=r"(a), "=r"(b), "=r"(c), "=r"(d) : "l"(p) : "memory");
}
__device__ __forceinline__ void st_b128(void* p, uint32_t a, uint32_t b, uint32_t c, uint32_t d) {
  asm volatile("{.reg .b128 t; .reg .b64 lo, hi; mov.b64 lo, {%1,%2}; mov.b64 hi, {%3,%4}; mov.b128 t, {lo, hi}; st.relaxed.gpu.global.b128 [%0], t;}"
               ::"l"(p), "r"(a), "r"(b), "r"(c), "r"(d) : "memory");
}
__device__ __forceinline__ void ld_v4(const void* p, uint32_t& a, uint32_t& b, uint32_t& c, uint32_t& d) {
  asm volatile("ld.relaxed.gpu.global.v4.u32 {%0,%1,%2,%3}, [%4];" : "=r"(a), "=r"(b), "=r"(c), "=r"(d) : "l"(p) : "memory");
}
__device__ __forceinline__ void st_u32(void* p, uint32_t v) { asm volatile("st.relaxed.gpu.global.u32 [%0], %1;" ::"l"(p), "r"(v) : "memory"); }
__device__ __forceinline__ void sts128(uint32_t a, uint32_t x, uint32_t y, uint32_t z, uint32_t w) {
  asm volatile("st.shared.v4.u32 [%0], {%1,%2,%3,%4};" ::"r"(a), "r"(x), "r"(y), "r"(z), "r"(w) : "memory");
}
__device__ __forceinline__ void lds128f(uint32_t a, float& x, float& y, float& z, float& w) {
  asm volatile("ld.shared.v4.f32 {%0,%1,%2,%3}, [%4];" : "=f"(x), "=f"(y), "=f"(z), "=f"(w) : "r"(a) : "memory");
}
__device__ __forceinline__ void sts32f(uint32_t a, float x) { asm volatile("st.shared.f32 [%0], %1;" ::"r"(a), "f"(x) : "memory"); }
__device__ __forceinline__ void lds64f(uint32_t a, float& x, float& y) { asm volatile("ld.shared.v2.f32 {%0,%1}, [%2];" : "=f"(x), "=f"(y) : "r"(a) : "memory"); }

__device__ __forceinline__ void st_v2(void* p, uint32_t a, uint32_t b) { asm volatile("st.relaxed.gpu.global.v2.u32 [%0], {%1,%2};" ::"l"(p), "r"(a), "r"(b) : "memory"); }
__device__ __forceinline__ void ld_v2(const void* p, uint32_t& a, uint32_t& b) { asm volatile("ld.relaxed.gpu.global.v2.u32 {%0,%1}, [%2];" : "=r"(a), "=r"(b) : "l"(p) : "memory"); }
__device__ __forceinline__ uint32_t ld_u32(const void* p) { uint32_t v; asm volatile("ld.relaxed.gpu.global.u32 %0, [%1];" : "=r"(v) : "l"(p) : "memory"); return v; }
__device__ __forceinline__ uint32_t ld_acq(const unsigned* p) { uint32_t v; asm volatile("ld.acquire.gpu.global.u32 %0, [%1];" : "=r"(v) : "l"(p) : "memory"); return v; }
__device__ __forceinline__ void lds128(uint32_t a, uint32_t& x, uint32_t& y, uint32_t& z, uint32_t& w) {
  asm volatile("ld.shared.v4.u32 {%0,%1,%2,%3}, [%4];" : "=r"(x), "=r"(y), "=r"(z), "=r"(w) : "r"(a) : "memory");
}
__device__ __forceinline__ void lds64(uint32_t a, uint32_t& x, uint32_t& y) { asm volatile("ld.shared.v2.u32 {%0,%1}, [%2];" : "=r"(x), "=r"(y) : "r"(a) : "memory"); }
__device__ __forceinline__ uint32_t lds32(uint32_t a) { uint32_t v; asm volatile("ld.shared.u32 %0, [%1];" : "=r"(v) : "r"(a) : "memory"); return v; }
__device__ __forceinline__ uint32_t lds32v(uint32_t a) { uint32_t v; asm volatile("ld.volatile.shared.u32 %0, [%1];" : "=r"(v) : "r"(a) : "memory"); return v; }
__device__ __forceinline__ void sts32(uint32_t a, uint32_t v) { asm volatile("st.shared.u32 [%0], %1;" ::"r"(a), "r"(v) : "memory"); }
__device__ __forceinline__ void sts64(uint32_t a, uint32_t x, uint32_t y) { asm volatile("st.shared.v2.u32 [%0], {%1,%2};" ::"r"(a), "r"(x), "r"(y) : "memory"); }
__device__ __forceinline__ uint32_t clk() { uint64_t c; asm volatile("mov.u64 %0, %%clock64;" : "=l"(c)::"memory"); return (uint32_t)c; }
__device__ __forceinline__ uint32_t gtime() { uint64_t c; asm volatile("mov.u64 %0, %%globaltimer;" : "=l"(c)::"memory"); return (uint32_t)c; }
__device__ __forceinline__ uint32_t gtime_after(uint32_t dep) {
  uint32_t t;
  asm volatile("{.reg .pred p; .reg .u64 c; setp.ne.u32 p, %1, 0x7fc12345; mov.u64 c, 0; @p mov.u64 c, %%globaltimer; cvt.u32.u64 %0, c;}" : "=r"(t) : "r"(dep) : "memory");
  return t;
}
__device__ __forceinline__ void spin_clk_until(uint32_t t) { while ((int)(clk() - t) < 0) {} }
__device__ __forceinline__ void spin_gt_until(uint32_t t) { while ((int)(gtime() - t) < 0) {} }
template <int L> __device__ __forceinline__ uint32_t lop3(uint32_t a, uint32_t b, uint32_t c) {
  uint32_t r; asm("lop3.b32 %0, %1, %2, %3, %4;" : "=r"(r) : "r"(a), "r"(b), "r"(c), "n"(L)); return r;
}
__device__ __forceinline__ float bf_lo(uint32_t w) { return __uint_as_float(w << 16); }
__device__ __forceinline__ float bf_hi(uint32_t w) { return __uint_as_float(w & 0xffff0000u); }
__device__ __forceinline__ uint32_t near_page(unsigned char* p) {
  int ba = 1 << 30, bb = 1 << 30;
  for (int r = 0; r < 5; r++) {
    const uint32_t t0 = clk();
    uint32_t u, v, t1, t2;
    asm volatile("atom.relaxed.gpu.global.exch.b32 %0, [%1], %2;" : "=r"(u) : "l"(p), "r"(r) : "memory");
    asm volatile("atom.relaxed.gpu.global.exch.b32 %0, [%1], %2;" : "=r"(v) : "l"(p + 4096), "r"(r) : "memory");
    asm volatile("{.reg .pred p; .reg .u64 c; setp.ne.u32 p, %1, 0x7fc12345; mov.u64 c, 0; @p mov.u64 c, %%clock64; cvt.u32.u64 %0, c;}" : "=r"(t1) : "r"(u) : "memory");
    asm volatile("{.reg .pred p; .reg .u64 c; setp.ne.u32 p, %1, 0x7fc12345; mov.u64 c, 0; @p mov.u64 c, %%clock64; cvt.u32.u64 %0, c;}" : "=r"(t2) : "r"(v) : "memory");
    ba = min(ba, (int)(t1 - t0));
    bb = min(bb, (int)(t2 - t0));
  }
  return bb - ba > 80 ? 0u : 4096u;
}

#define K_SPLIT 0
#define D1 4
#define D2 1
#define T_BAR 5
#define NOM 12
#define SPAN0 34
#define N20 17
#define TM0 8
#define MG1 32
#define MG2 40
#define ODLY 2
#define WARM 1
#define LOCP 32
#define PASS 24
#define FIXP 8
namespace rk {
constexpr uint32_t XT = 0;
constexpr uint32_t RA = 65536;
constexpr uint32_t KV = RA;
constexpr uint32_t QX = KV + 4 * 20480;
constexpr uint32_t WRES = RA + 14 * 8192;
constexpr uint32_t WOS = RA + 131072;
constexpr uint32_t OST = WOS;
constexpr uint32_t PS = WOS + 8192;
constexpr uint32_t MEMS = WOS + 16384;
constexpr uint32_t QM = MEMS + 8192;
constexpr uint32_t SC = QM + 2048;
constexpr uint32_t SR = SC + 1024;
constexpr uint32_t VM = QX;
constexpr uint32_t SF0 = PS + 4096, SF1 = VM + 8192;
constexpr uint32_t BAR = SR + 2048;
constexpr uint32_t B_QK = BAR, B_V = BAR + 120;
constexpr uint32_t B_KV = BAR + 8;
constexpr uint32_t B_XF = BAR + 40;
constexpr uint32_t B_W = BAR + 56;
constexpr uint32_t B_FREE = BAR + 88;
constexpr uint32_t B_OF = BAR + 96, B_PUB = BAR + 112;
constexpr uint32_t B_MEM = BAR + 128;
constexpr uint32_t B_Q = BAR + 160;
constexpr uint32_t B_OK = BAR + 192, B_FIX = BAR + 200;
constexpr uint32_t TK = BAR + 256;
constexpr uint32_t TK_X = TK + 48, TK_Q = TK + 56, TK_PG = TK + 64;
constexpr uint32_t TABS = BAR + 384;
constexpr uint32_t TM = BAR + 1024;
constexpr uint32_t SMEM = TM + 4096 + 1024;
constexpr int NB_P = 1, NB_T = 2, NB_S = 4, NB_TD = 5, NB_TAB = 6, NB_M = 7;
constexpr float kExpScale = 0.08838834764831845f * 1.4426950408889634f;
constexpr int kSplit = K_SPLIT;
}

__device__ __forceinline__ void r_proj_issue(const uint32_t (&w)[112], float (&d)[16], uint32_t sb, int seg, int warp, int j0, int j1) {
  using namespace rk;
  const uint64_t desc = make_desc(sb + XT + (seg & 1) * 32768, 16, 1024, 1);
  const uint64_t adesc = make_desc(sb + WRES + (warp >> 2) * 8192, 1024, 1024, 1);
  wg_fence();
#pragma unroll
  for (int i = 0; i < 32; i++) {
    if (i < j0 || i >= j1) continue;
    const int j = i < 8 ? i : (i - 8) % 6 == 0 ? 28 + (i - 8) / 6 : i - 1 - (i - 8) / 6;
    const uint64_t bd = desc + (uint64_t)(((j >> 2) * 4096 + (j & 3) * 32) >> 4);
    if (j < 28) wgmma_rs32<0>(d, w[4 * j], w[4 * j + 1], w[4 * j + 2], w[4 * j + 3], bd, j > 0);
    else wgmma_ss32<1, 0>(d, adesc + (uint64_t)((j - 28) * 128), bd, 1);
  }
  wg_commit();
}
__device__ __forceinline__ void r_store_rows(const float (&d)[16], uint32_t dst, int w4, uint32_t lane) {
  const uint32_t a = dst + ((lane >> 4) * 8 + (lane & 7)) * 128 + (((2 * w4 + ((lane >> 3) & 1)) ^ (lane & 7)) << 4);
  stsm4t(a, pack2(d[0], d[1]), pack2(d[2], d[3]), pack2(d[4], d[5]), pack2(d[6], d[7]));
  stsm4t(a + 2048, pack2(d[8], d[9]), pack2(d[10], d[11]), pack2(d[12], d[13]), pack2(d[14], d[15]));
}
template <bool R0>
__device__ __forceinline__ void r_proj_store(const float (&d)[16], uint32_t sb, int seg, int warp, uint32_t lane, uint32_t rank) {
  using namespace rk;
  if (R0) {
    r_store_rows(d, sb + QX + (seg & 3) * 8192 + (warp >> 2) * 4096, warp & 3, lane);
  } else {
    const uint32_t a = sb + KV + (seg & 3) * 20480 + (rank - 1) * 10240 + (lane >> 4) * 2048 + (16 * warp + (lane & 15)) * 16;
    stsm4(a, pack2(d[0], d[1]), pack2(d[2], d[3]), pack2(d[4], d[5]), pack2(d[6], d[7]));
    stsm4(a + 4096, pack2(d[8], d[9]), pack2(d[10], d[11]), pack2(d[12], d[13]), pack2(d[14], d[15]));
  }
  fence_async_smem();
}
__device__ __forceinline__ void r_proj_share(uint32_t sb, int seg, uint32_t rank) {
  using namespace rk;
  const uint32_t bar = sb + B_KV + 8 * (seg & 3), src = sb + KV + (seg & 3) * 20480 + (rank - 1) * 10240;
  if (rank != 0) {
    bulk_s2c(mapa(src, 3 - rank), src, 8192, mapa(bar, 3 - rank));
    bulk_s2c(mapa(src, 0), src, 8192, mapa(bar, 0));
  }
  mbar_arrive_tx(bar, rank == 0 ? 16384 : 8192);
}
__device__ __forceinline__ void r_flag_o(int seg) {
  asm volatile("cp.async.bulk.wait_group 0; red.relaxed.gpu.global.add.u32 [%0], 1;" ::"l"(&g_cnt[C_O + (seg >> 2)]) : "memory");
}

template <int I>
__device__ __forceinline__ void r_vo_issue(const uint32_t (&wo)[64], float (&d)[16], uint32_t sb, int seg) {
  using namespace rk;
  const uint64_t desc = make_desc(sb + KV + (seg & 3) * 20480 + 10240, 128, 2048, 0);
  const uint64_t adesc = make_desc(sb + WOS, 16, 1024, 1);
  wg_fence();
#pragma unroll
  for (int kk = 0; kk < 8; kk++) {
    if (I < 2) wgmma_rs32<1>(d, wo[32 * I + 4 * kk], wo[32 * I + 4 * kk + 1], wo[32 * I + 4 * kk + 2], wo[32 * I + 4 * kk + 3], desc + (uint64_t)(kk * 16), kk > 0);
    else wgmma_ss32<0, 1>(d, adesc + (uint64_t)(((kk >> 2) * 8192 + (kk & 3) * 32) >> 4), desc + (uint64_t)(kk * 16), kk > 0);
  }
  wg_commit();
}
__device__ __forceinline__ void r_vo_issue2(const uint32_t (&wo)[64], float (&d0)[16], float (&d2)[16], uint32_t sb, int seg) {
  using namespace rk;
  const uint64_t desc = make_desc(sb + KV + (seg & 3) * 20480 + 10240, 128, 2048, 0);
  const uint64_t adesc = make_desc(sb + WOS, 16, 1024, 1);
  wg_fence();
#pragma unroll
  for (int kk = 0; kk < 8; kk++) {
    wgmma_rs32<1>(d0, wo[4 * kk], wo[4 * kk + 1], wo[4 * kk + 2], wo[4 * kk + 3], desc + (uint64_t)(kk * 16), kk > 0);
    wgmma_ss32<0, 1>(d2, adesc + (uint64_t)(((kk >> 2) * 8192 + (kk & 3) * 32) >> 4), desc + (uint64_t)(kk * 16), kk > 0);
  }
  wg_commit();
}
__device__ __forceinline__ void pack16(uint32_t* o, const float (&d)[16]) {
#pragma unroll
  for (int j = 0; j < 8; j++) o[j] = pack2(d[2 * j], d[2 * j + 1]);
}

template <int NT>
__device__ __forceinline__ void r_attn_role(uint32_t sb, int tw, int lane, uint32_t rank, uint32_t head, const bf16* __restrict__ Wo) {
  using namespace rk;
  const int g = lane >> 2, t = lane & 3;
  const int tile0 = (NT == 2 ? 0 : 12 * (int)rank - 4) + tw;
  uint32_t wo[64];
  const uint32_t woa = sb + WOS + (16 * tw + (lane & 15)) * 128;
  const uint32_t wx = (lane >> 4) ^ (lane & 7);
  {
    uint32_t wt[32 * NT];
#pragma unroll
    for (int i = 0; i < NT; i++) {
      const uint32_t* src = reinterpret_cast<const uint32_t*>(Wo + (size_t)(head * 128 + 2 * t) * kD + (tile0 + 4 * i) * 16 + 2 * g);
#pragma unroll
      for (int kk = 0; kk < 8; kk++) {
        wt[32 * i + 4 * kk] = __ldg(src + (16 * kk) * (kD / 2));
        wt[32 * i + 4 * kk + 1] = __ldg(src + (16 * kk + 1) * (kD / 2));
        wt[32 * i + 4 * kk + 2] = __ldg(src + (16 * kk + 8) * (kD / 2));
        wt[32 * i + 4 * kk + 3] = __ldg(src + (16 * kk + 9) * (kD / 2));
      }
    }
#pragma unroll
    for (int j = 0; j < 16 * NT; j++) {
      const uint32_t x = wt[2 * j], y = wt[2 * j + 1];
      wt[2 * j] = __byte_perm(x, y, 0x5410);
      wt[2 * j + 1] = __byte_perm(x, y, 0x7632);
    }
#pragma unroll
    for (int j = 0; j < 64; j++) wo[j] = wt[j];
    if (NT == 3) {
#pragma unroll
      for (int kk = 0; kk < 8; kk++)
        stsm4(woa + (kk >> 2) * 8192 + (((2 * (kk & 3)) ^ wx) << 4), wt[32 * NT - 32 + 4 * kk], wt[32 * NT - 31 + 4 * kk], wt[32 * NT - 30 + 4 * kk], wt[32 * NT - 29 + 4 * kk]);
    } else if (tw == 0) {
      sts128(sb + PS + 5 * 512 + lane * 16, 0u, 0u, 0u, 0u);
    }
    fence_async_smem();
    bar_sync(NB_T, 128);
  }
  uint64_t mail[NT];
  bar_sync(NB_TAB, 512);
#pragma unroll
  for (int i = 0; i < NT; i++) {
    const uint32_t unit = (tile0 + 4 * i) * 4 + (g >> 2) * 2 + (t >> 1);
    mail[i] = (uint64_t)(g_mail + (unit * 8192 + (lds32(sb + TABS + unit * 4) & 4096u) + head * 64 + (t & 1) * 32 + (g & 3) * 8));
  }
  uint32_t vox[8 * NT];
  uint32_t la = sb + lane * 16;
  OPAQUE(la);
  const uint32_t vma = la + VM + tw * 512;
  mbar_wait(sb + B_KV, 0);
  if (NT == 3) {
    sts128(vma, (uint32_t)mail[0], (uint32_t)(mail[0] >> 32), (uint32_t)mail[1], (uint32_t)(mail[1] >> 32));
    sts64(vma + 2048, (uint32_t)mail[NT - 1], (uint32_t)(mail[NT - 1] >> 32));
  }
  {
    float d[16];
    r_vo_issue<0>(wo, d, sb, 0); wg_wait<0>(); pack16(vox, d);
    r_vo_issue<1>(wo, d, sb, 0); wg_wait<0>(); pack16(vox + 8, d);
    if (NT == 3) { r_vo_issue<2>(wo, d, sb, 0); wg_wait<0>(); pack16(vox + 8 * NT - 8, d); }
  }
  for (int s = 0;; s++) {
    {
      uint32_t redo = 0;
      bool pend = true;
      mbar_wait(sb + B_V, s & 1);
      while (true) {
        constexpr uint32_t kOnes = 0x3F803F80u;
        const uint32_t va = la + (la & 256) * 3 + KV + (s & 3) * 20480 + 10240 + 8192;
        float vm[4][4];
        uint32_t b[16], dep = 0;
#pragma unroll
        for (int kk = 0; kk < 4; kk++) ldsm4t(va + kk * 256, b[4 * kk], b[4 * kk + 1], b[4 * kk + 2], b[4 * kk + 3]);
        TMARKD(tw == 0, 3, b[0]);
#pragma unroll
        for (int kk = 0; kk < 4; kk++) {
          if (kk == T_BAR) dep = __float_as_uint(vm[3][0]);
#pragma unroll
          for (int c = 0; c < 4; c++) {
            const uint32_t* p = &wo[16 * c + 4 * kk];
            const uint32_t* q = &b[4 * kk + 2 * (c & 1)];
            if (kk == 0) mma16z(vm[c], p[0], p[1], p[2], p[3], q[0], q[1]);
            else mma16(vm[c], p[0], p[1], p[2], p[3], q[0], q[1]);
          }
        }
        if (T_BAR == 4) dep = __float_as_uint(vm[3][0]);
        uint32_t vp[4];
#pragma unroll
        for (int i = 0; i < 2; i++) {
          vp[2 * i] = pack2(vm[2 * i][0] + vm[2 * i + 1][0], vm[2 * i][1] + vm[2 * i + 1][1]);
          vp[2 * i + 1] = pack2(vm[2 * i][2] + vm[2 * i + 1][2], vm[2 * i][3] + vm[2 * i + 1][3]);
        }
        if (T_BAR == 5) dep = vp[0] | vp[1] | vp[2] | vp[3];
        bar_sync_after(NB_S, NT == 3 ? 480 : 224, dep, redo);
        uint32_t p[6], v3[4];
        ldsm4t(la + redo + SC, p[0], p[1], p[2], p[3]);
        ldsm2t(((la + redo) & ~0x180u) + SC + 512, p[4], p[5]);
        if (NT == 3) lds128(vma + 4096, v3[0], v3[1], v3[2], v3[3]);
        TMARKD(tw == 0, 4, p[0]);
        float o[NT][4], sa[4], sc[4];
        mma16z(sa, kOnes, kOnes, kOnes, kOnes, p[0], p[1]);
        mma16z(sc, kOnes, kOnes, kOnes, kOnes, p[2], p[3]);
#pragma unroll
        for (int i = 0; i < 2; i++) mma8z(o[i], vp[2 * i], vp[2 * i + 1], p[4]);
        if (NT == 3) mma16z(o[NT - 1], v3[0], v3[1], v3[2], v3[3], p[4], p[5]);
        mma8(sa, kOnes, kOnes, p[4]);
#pragma unroll
        for (int i = 0; i < NT; i++) mma16(o[i], vox[8 * i], vox[8 * i + 1], vox[8 * i + 2], vox[8 * i + 3], p[0], p[1]);
        if (NT == 3) {
          asm volatile("ld.shared.v2.u64 {%0,%1}, [%2];" : "=l"(mail[0]), "=l"(mail[1]) : "r"(vma) : "memory");
          asm volatile("ld.shared.u64 %0, [%1];" : "=l"(mail[NT - 1]) : "r"(vma + 2048) : "memory");
        }
#pragma unroll
        for (int i = 0; i < NT; i++) mma16(o[i], vox[8 * i + 4], vox[8 * i + 5], vox[8 * i + 6], vox[8 * i + 7], p[2], p[3]);
        const float s0 = sa[0] + sc[0], s1 = sa[1] + sc[1];
        const float i0 = rcp(s0), i1 = rcp(s1);
        const bool ok = redo ? pend : max(__float_as_uint(s0) - 0x30000000u, __float_as_uint(s1) - 0x30000000u) < 0x1F000000u;
        const uint32_t tag = (s + 1) & 1;
#pragma unroll
        for (int i = 0; i < NT; i++)
          asm volatile("{.reg .pred q; setp.ne.u32 q, %3, 0; @q st.relaxed.gpu.global.v2.u32 [%0], {%1,%2};}" ::"l"(mail[i]),
                       "r"(lop3<0xea>(pack2(o[i][0] * i0, o[i][2] * i0), ~1u, tag)), "r"(pack2(o[i][1] * i1, o[i][3] * i1)), "r"((uint32_t)ok) : "memory");
        if (redo) break;
        if (NT == 3) bar_arrive(NB_TD, 384);
        sts32(sb + TK + tw * 4, gtime_after(ok));
        if (NT == 3 && lane == 0) mbar_arrive(sb + B_PUB);
        TMARKD(tw == 0, 5, ok);
        if (__all_sync(~0u, ok)) break;
        float sv[10];
        const uint32_t ra = sb + SR + t * 128 + (g >> 1) * 16 + (g & 1) * 4;
#pragma unroll
        for (int j = 0; j < 8; j++) sv[j] = __uint_as_float(lds32(ra + (j >> 2) * 512 + ((j >> 1) & 1) * 8 + (j & 1) * 64));
#pragma unroll
        for (int j = 0; j < 2; j++) sv[8 + j] = __uint_as_float(lds32(ra + 1024 + j * 64));
        float m = sv[0];
#pragma unroll
        for (int j = 1; j < 10; j++) m = fmaxf(m, sv[j]);
        m = fmaxf(m, __shfl_xor_sync(~0u, m, 1));
        const float mb = -fmaxf(m, __shfl_xor_sync(~0u, m, 2)) * kExpScale;
#pragma unroll
        for (int j = 0; j < 5; j++) p[j] = pack2(ex2(fmaf(sv[2 * j], kExpScale, mb)), ex2(fmaf(sv[2 * j + 1], kExpScale, mb)));
        redo = (NT == 2 ? SF0 : SF1) - SC + tw * 1024;
        pend = !ok;
        stsm4t(la + redo + SC, p[0], p[1], p[2], p[3]);
        stsm1t(la + redo + SC + 512, p[4]);
        __syncwarp();
      }
      if (tw == 0 && lane == 0) {
        mbar_arrive_tx(sb + B_QK, rank == 2 ? 4096 : 2048);
        mbar_arrive_tx(sb + B_V, rank == 2 ? 0 : 2048);
      }
    }
    if (NT == 3) {
      if (s + 1 == kNSeg) break;
      mbar_wait(sb + B_KV + 8 * ((s + 1) & 3), ((s + 1) >> 2) & 1);
      float d0[16], d1[16];
      r_vo_issue2(wo, d0, d1, sb, s + 1);
      wg_wait<0>();
      pack16(vox, d0);
      r_vo_issue<1>(wo, d0, sb, s + 1);
      pack16(vox + 8 * NT - 8, d1);
      wg_wait<0>();
      pack16(vox + 8, d0);
    } else {
      float sc[20], d0[16], d1[16];
      mbar_wait(sb + B_Q + 8 * (s & 3), (s >> 2) & 1);
      {
        const uint64_t qd = make_desc(sb + QX + (s & 3) * 8192, 16, 1024, 1), kd = make_desc(sb + KV + (s & 3) * 20480, 128, 2048, 0);
        wg_fence();
#pragma unroll
        for (int kk = 0; kk < 8; kk++) wgmma_ss40(sc, qd + (uint64_t)(((kk >> 2) * 4096 + (kk & 3) * 32) >> 4), kd + (uint64_t)(kk * 16), kk > 0);
        wg_commit();
        wg_wait<0>();
      }
      if (tw < 2) {
        const int dl = 16 * tw + g - 2 * t;
        float m0 = fmaxf(sc[16], sc[17]), m1 = fmaxf(sc[18], sc[19]);
#pragma unroll
        for (int n = 0; n < 4; n++) {
          if (8 * n > dl) sc[4 * n] = -INFINITY;
          if (8 * n + 1 > dl) sc[4 * n + 1] = -INFINITY;
          if (8 * n - 8 > dl) sc[4 * n + 2] = -INFINITY;
          if (8 * n - 7 > dl) sc[4 * n + 3] = -INFINITY;
          m0 = fmaxf(m0, fmaxf(sc[4 * n], sc[4 * n + 1]));
          m1 = fmaxf(m1, fmaxf(sc[4 * n + 2], sc[4 * n + 3]));
        }
        m0 = fmaxf(m0, __shfl_xor_sync(~0u, m0, 1)); m1 = fmaxf(m1, __shfl_xor_sync(~0u, m1, 1));
        m0 = fmaxf(m0, __shfl_xor_sync(~0u, m0, 2)); m1 = fmaxf(m1, __shfl_xor_sync(~0u, m1, 2));
        m0 *= -kExpScale; m1 *= -kExpScale;
        float s0 = 0.f, s1 = 0.f;
#pragma unroll
        for (int n = 0; n < 5; n++) {
          sc[4 * n] = ex2(fmaf(sc[4 * n], kExpScale, m0)); sc[4 * n + 1] = ex2(fmaf(sc[4 * n + 1], kExpScale, m0));
          sc[4 * n + 2] = ex2(fmaf(sc[4 * n + 2], kExpScale, m1)); sc[4 * n + 3] = ex2(fmaf(sc[4 * n + 3], kExpScale, m1));
          s0 += sc[4 * n] + sc[4 * n + 1]; s1 += sc[4 * n + 2] + sc[4 * n + 3];
        }
        s0 += __shfl_xor_sync(~0u, s0, 1); s1 += __shfl_xor_sync(~0u, s1, 1);
        s0 += __shfl_xor_sync(~0u, s0, 2); s1 += __shfl_xor_sync(~0u, s1, 2);
        const float i0 = rcp(s0), i1 = rcp(s1);
        uint32_t p[10];
#pragma unroll
        for (int n = 0; n < 5; n++) { p[2 * n] = pack2(sc[4 * n] * i0, sc[4 * n + 1] * i0); p[2 * n + 1] = pack2(sc[4 * n + 2] * i1, sc[4 * n + 3] * i1); }
        const uint32_t pa = sb + PS + (lane >> 4) * 512 + (16 * tw + (lane & 15)) * 16;
        stsm4(pa, p[0], p[1], p[2], p[3]);
        stsm4(pa + 1024, p[4], p[5], p[6], p[7]);
        stsm2(pa + 2048, p[8], p[9]);
        fence_async_smem();
      }
      TMARKD(tw == 0, 10, 0);
      bar_sync(NB_T, 128);
      if (s + 1 < kNSeg) {
        mbar_wait(sb + B_KV + 8 * ((s + 1) & 3), ((s + 1) >> 2) & 1);
        mbar_wait(sb + B_PUB, s & 1);
      }
      {
        const uint32_t vb = sb + KV + (s & 3) * 20480 + 10240;
        const uint64_t pd = make_desc(sb + PS, 512, 128, 0);
        const uint64_t vd = make_desc(vb, 2048, 128, 0), vd2 = make_desc(vb + 8192, 0, 128, 0);
        wg_fence();
        wgmma_ss32<0, 0>(d0, vd, pd, 0);
        wgmma_ss32<0, 0>(d1, vd + 64, pd, 0);
        wgmma_ss32<0, 0>(d0, vd + 256, pd + 64, 1);
        wgmma_ss32<0, 0>(d1, vd + 256 + 64, pd + 64, 1);
        wgmma_ss32<0, 0>(d0, vd2, pd + 128, 1);
        wgmma_ss32<0, 0>(d1, vd2 + 64, pd + 128, 1);
        wg_commit();
      }
      wg_wait<0>();
      r_store_rows(d0, sb + OST, tw, lane);
      r_store_rows(d1, sb + OST + 4096, tw, lane);
      r_vo_issue<0>(wo, d0, sb, s + 1);
      fence_async_smem();
      __syncwarp();
      if (lane == 0) mbar_arrive(sb + B_OF);
      r_vo_issue<1>(wo, d1, sb, s + 1);
      wg_wait<0>();
      if (s + 1 == kNSeg) break;
      pack16(vox, d0);
      pack16(vox + 8, d1);
    }
    TMARKD(tw == 0, 6, vox[8 * NT - 1]);
  }
}

__device__ __forceinline__ void r_score_role(uint32_t sb, int mw, int lane, uint32_t nbar) {
  using namespace rk;
  for (int s = 0; s < kNSeg; s++) {
    uint32_t ln = lane;
    OPAQUE(ln);
    const uint32_t ka = sb + KV + (s & 3) * 20480 + (2 * mw + ((ln >> 3) & 1)) * 2048 + ((ln >> 4) * 8 + (ln & 7)) * 16;
    const uint32_t qa = sb + QM + ln * 16;
    uint32_t kf[32], q[16];
    mbar_wait(sb + B_KV + 8 * (s & 3), (s >> 2) & 1);
#pragma unroll
    for (int j = 0; j < 8; j++) ldsm4t(ka + j * 256, kf[4 * j], kf[4 * j + 1], kf[4 * j + 2], kf[4 * j + 3]);
    mbar_wait(sb + B_QK, s & 1);
#pragma unroll
    for (int i = 0; i < 4; i++) ldsm4t(qa + i * 512, q[4 * i], q[4 * i + 1], q[4 * i + 2], q[4 * i + 3]);
    float c[4][4];
#pragma unroll
    for (int j = 0; j < 4; j++) mma16z(c[j], kf[4 * j], kf[4 * j + 1], kf[4 * j + 2], kf[4 * j + 3], q[2 * j], q[2 * j + 1]);
#pragma unroll
    for (int j = 4; j < 8; j++) mma16(c[j - 4], kf[4 * j], kf[4 * j + 1], kf[4 * j + 2], kf[4 * j + 3], q[2 * j], q[2 * j + 1]);
    float v[4];
#pragma unroll
    for (int i = 0; i < 4; i++) v[i] = (c[0][i] + c[1][i]) + (c[2][i] + c[3][i]);
    sts128(qa + (SR - QM) + mw * 512, __float_as_uint(v[0]), __float_as_uint(v[1]), __float_as_uint(v[2]), __float_as_uint(v[3]));
    stsm2(qa + (SC - QM) + mw * 256, pack2(ex2(v[0] * kExpScale), ex2(v[1] * kExpScale)), pack2(ex2(v[2] * kExpScale), ex2(v[3] * kExpScale)));
    bar_arrive(NB_S, nbar);
    TMARKD(mw == 0, 13, 0);
  }
}

__device__ __forceinline__ void r_mscore_role(uint32_t sb, int lane, uint32_t rank, uint32_t head, const CUtensorMap* tmX) {
  using namespace rk;
  const uint32_t qa = sb + QM + lane * 16;
  const uint32_t ep = ld_u32(&g_cnt[C_O + 15]) / 128 + 1;
  uint32_t local = 7;
  for (int s = 0; s < kNSeg; s++) {
    const uint32_t ka = sb + KV + (s & 3) * 20480 + 8192 + (((lane >> 3) & 1) * 2 + (lane >> 4)) * 128 + (lane & 7) * 16;
    uint32_t km[16], q[16];
    mbar_wait(sb + B_QK, s & 1);
#pragma unroll
    for (int i = 0; i < 4; i++) {
      ldsm4t(ka + i * 512, km[4 * i], km[4 * i + 1], km[4 * i + 2], km[4 * i + 3]);
      ldsm4t(qa + i * 512, q[4 * i], q[4 * i + 1], q[4 * i + 2], q[4 * i + 3]);
    }
    float c[4][4];
#pragma unroll
    for (int j = 0; j < 4; j++) mma16z(c[j], km[4 * (j >> 1)], km[4 * (j >> 1) + 1], km[4 * (j >> 1) + 2], km[4 * (j >> 1) + 3], q[2 * j], q[2 * j + 1]);
#pragma unroll
    for (int j = 4; j < 8; j++) mma16(c[j - 4], km[4 * (j >> 1)], km[4 * (j >> 1) + 1], km[4 * (j >> 1) + 2], km[4 * (j >> 1) + 3], q[2 * j], q[2 * j + 1]);
    const float v0 = (c[0][0] + c[1][2]) + (c[2][0] + c[3][2]), v1 = (c[0][1] + c[1][3]) + (c[2][1] + c[3][3]);
    sts64(qa + (SR - QM) + 1024, __float_as_uint(v0), __float_as_uint(v1));
    sts32(sb + SC + 512 + lane * 4, pack2(ex2(v0 * kExpScale), ex2(v1 * kExpScale)));
    bar_arrive(NB_S, rank == 0 ? 224 : 480);
    TMARKD(1, 19, 0);
    if (lane == 0) {
      mbar_wait(sb + B_V, s & 1);
      const int sn = s + (rank == 0 ? 3 : 4);
      const uint32_t xf = sb + B_XF + 8 * (sn & 1);
      bool ready = false;
      if (rank == 0) {
        local >>= 1;
        if (local & 1) mbar_arrive(sb + B_Q + 8 * ((s + 1) & 3));
        if (s) r_flag_o(s - 1);
        if (sn < kNSeg) {
          ready = (int)(ld_acq(&g_cnt[C_Q + (sn >> 2) * 16 + (head >> 1)]) - ep) >= 0;
          sts32(sb + TK_Q + (sn & 1) * 4, ready);
          if (ready) {
            const bf16* src = g_q + (size_t)((sn >> 2) * 64 + head * 2) * 8192 + (sn & 3) * 2048;
            const uint32_t bq = sb + B_Q + 8 * (sn & 3), dst = sb + QX + (sn & 3) * 8192;
            asm volatile("fence.proxy.async.global;" ::: "memory");
            mbar_arrive_tx(bq, 8192);
            bulk_g2s(dst, src, 4096, bq);
            bulk_g2s(dst + 4096, src + 8192, 4096, bq);
            mbar_arrive(xf);
          } else {
            local |= 4;
          }
        }
      }
      if (sn < kNSeg && !ready) {
        mbar_arrive_tx(xf, 32768);
        tma_3d(sb + XT + (sn & 1) * 32768, tmX, 0, sn * 32, 0, xf);
      }
      if (rank) mbar_wait(sb + B_PUB, s & 1);
      if (s + 2 < kNSeg) r_proj_share(sb, s + 2, rank);
      if (rank == 0) {
        mbar_wait(sb + B_OF, s & 1);
        spin_gt_until(lds32(sb + TK_X + 4));
        bf16* dst = g_o + (size_t)((s >> 2) * 64 + head * 2) * 8192 + (s & 3) * 2048;
        bulk_s2g(dst, sb + OST, 4096);
        bulk_s2g(dst + 8192, sb + OST + 4096, 4096);
        asm volatile("cp.async.bulk.commit_group; cp.async.bulk.wait_group.read 0;" ::: "memory");
      }
    }
    if (s == 5 && rank == 0 && lane < 4) st_u32(&g_tab[head * 4 + lane], 0u);
    __syncwarp();
  }
  if (rank == 0 && lane == 0) {
    r_flag_o(kNSeg - 1);
    TSTAMP(1, blockIdx.x * 80 + 3);
  }
}

__device__ __forceinline__ void r_timer_role(uint32_t sb, int lane, bool red) {
  using namespace rk;
  int span = SPAN0 * 16, n2 = N20 * 16;
  unsigned char* anc = g_pub + 3584;
  if (lane == 0) mbar_arrive(sb + B_OK);
  uint32_t stat = 0, fix = 0, x2 = 0;
  bool calm = false;
  mbar_wait(sb + B_QK, 0);
  mbar_wait(sb + B_V, 0);
  uint32_t tm = (gtime() >> 5) - TM0;
  for (int s = 0;; s++) {
    TSTAMP(lane == 0, blockIdx.x * 80 + 8 + s);
    if (s + 1 == kNSeg) break;
    const uint32_t tg = (uint32_t)(s + 1) << 24;
    if (lane < 2) st_u32(anc + (s & 1) * 8192 + lane * 4096 + blockIdx.x * 4, tg | stat | (tm & 4095u));
    uint32_t an[4], pg[4];
    const unsigned char* anr = anc + (s & 1) * 8192 + lds32(sb + TK_PG + (s & 1) * 4) + min(lane, 23) * 16;
    lds128(sb + TK_PG + (s & 1) * 16, pg[0], pg[1], pg[2], pg[3]);
    mbar_wait(sb + B_QK, s & 1);
    mbar_wait(sb + B_V, s & 1);
    int budget = 1 << 18;
    do {
      spend(budget);
      ld_v4(anr, an[0], an[1], an[2], an[3]);
    } while (__any_sync(~0u, max(max(an[0] - tg, an[1] - tg), max(an[2] - tg, an[3] - tg)) >= (1u << 24)));
    TMARKV(1, 29, (1 << 18) - 1 - budget);
    int dm = -2048;
#pragma unroll
    for (int i = 0; i < 4; i++) dm = max(dm, (int)((an[i] - tm) << 20) >> 20);
    tm += __reduce_max_sync(~0u, dm);
    const int sp = span >> 4;
    const uint32_t x1 = tm + sp;
    sts32(sb + TK_X, x1 << 5);
    if (red) bar_arrive(NB_M, 288);
    TMARKD(1, 17, x1);
    const int need = (__reduce_max_sync(~0u, max(max(an[0], an[1]), max(an[2], an[3]))) >> 18) & 63;
    const int mpub = __reduce_max_sync(~0u, max(max(an[0] & 0x3f000u, an[1] & 0x3f000u), max(an[2] & 0x3f000u, an[3] & 0x3f000u))) >> 12;
    TMARKV(1, 26, need); TMARKV(1, 27, mpub);
    if (s > WARM) {
      const int sh = s < 8 ? 1 : 3;
      if (calm) span += (min(need, sp + 3) * 16 + MG1 - span) >> sh;
      n2 += (min(mpub, (n2 >> 4) + 2) * 16 + MG2 - n2) >> sh;
    }
    calm = (int)(tm - x2) <= NOM + 1;
    x2 = x1 + (n2 >> 4);
    sts32(sb + TK_X + 4, (x2 + ODLY) << 5);
    TMARKV(1, 20, x1 << 5); TMARKV(1, 21, x2 << 5);
    const unsigned char* pp = g_pub + (s & 1) * 32768;
    const uint32_t late = x2 + (red && !lds32(sb + TK_Q + (s & 1) * 4) ? LOCP : NOM);
    uint32_t t2 = x2 << 5, bar = sb + B_MEM, par = (s + 1) & 1, tf = 0;
    OPAQUE(t2);
    if (lane < 4) mbar_arrive_tx(bar + 8 * lane, lane < 2 ? 1024 : 1024 << (lane - 1));
    mbar_wait(sb + B_PUB, s & 1);
    for (budget = 1 << 18;;) {
      spin_gt_until(t2);
      asm volatile("{.reg .pred p; elect.sync _|p, 0xffffffff;\n"
                   "@p cp.async.bulk.shared::cluster.global.mbarrier::complete_tx::bytes [%0 + 7168], [%2 + 1024], 1024, [%1];\n"
                   "@p cp.async.bulk.shared::cluster.global.mbarrier::complete_tx::bytes [%0 + 6144], [%2], 1024, [%1 + 8];\n"
                   "@p cp.async.bulk.shared::cluster.global.mbarrier::complete_tx::bytes [%0], [%3], 2048, [%1 + 16];\n"
                   "@p cp.async.bulk.shared::cluster.global.mbarrier::complete_tx::bytes [%0 + 2048], [%4], 2048, [%1 + 24];\n"
                   "@p cp.async.bulk.shared::cluster.global.mbarrier::complete_tx::bytes [%0 + 4096], [%5], 2048, [%1 + 24];}"
                   ::"r"(sb + MEMS), "r"(bar), "l"(pp + (3 * 8192 + pg[3])), "l"(pp + pg[0]), "l"(pp + (8192 + pg[1])), "l"(pp + (2 * 8192 + pg[2])) : "memory");
      TMARKD(!tf, 8, 0);
      const int e = (int)(lds32(sb + TK + min(lane, red ? 11 : 3) * 4) - (x1 << 5)) >> 5;
      const int post = __reduce_max_sync(~0u, lane < 4 ? e : -64) + sp + D1, pub = __reduce_max_sync(~0u, e) + D2;
      stat = min(max(post, 0), 63) << 18 | min(max(pub, 0), 63) << 12;
#pragma unroll
      for (int i = 3; i >= 0; i--) mbar_wait(bar + 8 * i, par);
      tm = gtime();
      TMARKD(1, 11, 0);
      uint32_t m = 0;
#pragma unroll
      for (int i = 0; i < 8; i++) m = max(m, lds32v(sb + MEMS + i * 1024 + lane * 32 + (lane >> 2) * 4));
      const bool bad = __any_sync(~0u, m == ~0u);
      if (bad && lane < 4) mbar_arrive_tx(sb + B_FIX + 8 * lane, lane < 2 ? 1024 : 1024 << (lane - 1));
      if (!bad) break;
      spend(budget);
      tf = tf ? tf : tm | 1u;
      bar = sb + B_FIX; par = fix; fix ^= 1;
      TMARKV(1, 30, (1 << 18) - budget);
    }
    tm = (tf ? tf + max((int)(tm - tf) + 32 * FIXP, 32 * PASS) : tm) >> 5;
    if (lane == 0) mbar_arrive(sb + B_OK);
    if ((int)((late - tm) << 5) > 0) tm = late;
  }
}

template <bool R0>
__device__ __forceinline__ void r_proj_role(uint32_t sb, int warp, int lane, uint32_t rank, uint32_t head, const CUtensorMap* tmX) {
  using namespace rk;
  uint32_t w[112];
  {
    const uint32_t wa = sb + RA + (warp >> 2) * 8192 + ((lane >> 4) * 8 + (lane & 7)) * 128 + (((2 * (warp & 3) + ((lane >> 3) & 1)) ^ (lane & 7)) << 4);
#pragma unroll
    for (int c = 0; c < 4; c++) {
      mbar_wait(sb + B_W + 8 * c, 0);
#pragma unroll
      for (int jj = 0; jj < 8; jj++) {
        const int j = 8 * c + jj;
        if (j < 28) ldsm4t(wa + (j >> 2) * 16384 + (j & 3) * 2048, w[4 * j], w[4 * j + 1], w[4 * j + 2], w[4 * j + 3]);
      }
    }
  }
  __syncwarp();
  TSTAMP(threadIdx.x == 0, blockIdx.x * 80 + 1);
  if (lane < 3) mbar_arrive_remote(mapa(sb + B_FREE, lane));
  mbar_wait_cl(sb + B_FREE, 0);
  constexpr int LA = R0 ? 2 : 3;
  for (int sg = 0; sg < LA; sg++) {
    float d[16];
    mbar_wait(sb + B_XF + 8 * (sg & 1), sg >> 1);
    r_proj_issue(w, d, sb, sg, warp, 0, 32);
    wg_wait<0>();
    r_proj_store<R0>(d, sb, sg, warp, lane, rank);
    bar_sync(NB_P, 256);
    if (threadIdx.x == 0 && sg < 2) {
      r_proj_share(sb, sg, rank);
      if (R0 && sg == 0) mbar_arrive(sb + B_Q);
      if (sg < LA - 1) {
        mbar_arrive_tx(sb + B_XF + 8 * sg, 32768);
        tma_3d(sb + XT + sg * 32768, tmX, 0, 64 + 32 * sg, 0, sb + B_XF + 8 * sg);
      }
    }
  }
  TSTAMP(threadIdx.x == 0, blockIdx.x * 80 + 2);
  const uint32_t xbar = rank == 2 ? B_V : B_QK;
  for (int s = 0; s < kNSeg; s++) {
    bool check = s > 0, pend = true, wpend = true;
    uint32_t ln, a3[16], bar0 = sb + B_MEM;
    while (true) {
      float c0[4], c1[4];
      uint32_t wx[16], b[16][4];
      ln = lane;
      OPAQUE(ln);
      {
        const uint32_t wr = sb + WRES + (warp >> 2) * 8192 + ((ln >> 4) * 8 + (ln & 7)) * 128 + (((2 * (warp & 3) + ((ln >> 3) & 1)) ^ (ln & 7)) << 4);
#pragma unroll
        for (int j = 0; j < 4; j++) ldsm4t(wr + j * 2048, wx[4 * j], wx[4 * j + 1], wx[4 * j + 2], wx[4 * j + 3]);
      }
      const uint32_t ma = sb + MEMS + ln * 16;
      const uint32_t dst = (R0 ? QM : KV + (rank - 1) * 10240 + 8192 + (s & 3) * 20480) + 256 * warp + 4 * ln;
      auto ldb = [&](int i) { ldsm4(ma + i * 512, b[i][0], b[i][1], b[i][2], b[i][3]); };
      auto mm = [&](int i) {
        mma16(c0, w[8 * i], w[8 * i + 1], w[8 * i + 2], w[8 * i + 3], b[i][0], b[i][1]);
        mma16(c1, w[8 * i + 4], w[8 * i + 5], w[8 * i + 6], w[8 * i + 7], b[i][2], b[i][3]);
      };
      TMARKW(1, 9 + warp, wx[15]);
      mbar_wait(bar0, s & 1);
      ldb(14); ldb(15);
      mbar_wait(sb + B_MEM + 8, s & 1);
      ldb(12);
      TMARKD(warp == 0, 0, b[14][0]);
      mma16z(c0, wx[0], wx[1], wx[2], wx[3], b[14][0], b[14][1]);
      mma16z(c1, wx[4], wx[5], wx[6], wx[7], b[14][2], b[14][3]);
      ldb(13);
      bool rdy = mbar_try(sb + B_MEM + 16, s & 1);
      mma16(c0, wx[8], wx[9], wx[10], wx[11], b[15][0], b[15][1]);
      mma16(c1, wx[12], wx[13], wx[14], wx[15], b[15][2], b[15][3]);
      if (!rdy) mbar_wait(sb + B_MEM + 16, s & 1);
      ldb(0); ldb(1);
      mm(12); ldb(2);
      mm(13); ldb(3);
      rdy = mbar_try(sb + B_MEM + 24, s & 1);
      mm(0);
      if (!rdy) mbar_wait(sb + B_MEM + 24, s & 1);
#pragma unroll
      for (int i = 1; i < 12; i++) {
        if (i + 3 < 12) ldb(i + 3);
        mm(i);
      }
      const float v0 = c0[0] + c1[0], v1 = c0[1] + c1[1];
      const uint32_t r0 = pack2(v0, v1), r1 = pack2(c0[2] + c1[2], c0[3] + c1[3]);
      const bool bad = check && pend && (v0 != v0 || v1 != v1);
      if (pend && !bad) {
#pragma unroll
        for (uint32_t d = 0; d < 2; d++) {
          const uint32_t base = mapa(sb, (rank + 1 + d) % 3u);
          st_async32(base + dst, r0, base + xbar);
          st_async32(base + dst + 128, r1, base + xbar);
        }
        sts32(sb + dst, r0);
        sts32(sb + dst + 128, r1);
      }
      const bool wbad = __any_sync(~0u, bad);
      if (ln == 0 && wpend && !wbad) mbar_arrive(sb + xbar);
      TMARKD(warp == 0, 1, r1);
      TMARKD(warp == 7, 12, r1);
      if (!R0) {
        const uint32_t woa = sb + WOS + (warp >> 2) * 8192 + (16 * (warp & 3) + (ln & 15)) * 128 + (((ln >> 4) ^ (ln & 7)) << 4);
#pragma unroll
        for (int kk = 0; kk < 4; kk++) ldsm4(woa ^ (kk << 5), a3[4 * kk], a3[4 * kk + 1], a3[4 * kk + 2], a3[4 * kk + 3]);
      }
      if (!bar_red_or(NB_P, 256, bad)) break;
      pend = bad; wpend = wbad;
      TMARKV(warp == 0, 28, 1);
      const bool first = bar0 != sb + B_OK;
      bar0 = sb + B_OK;
      if (first) continue;
      check = false;
      const unsigned char* pp = g_pub + (((s - 1) & 1) * 32768 + (warp >> 1) * 8192 + (warp & 1) * 1024 + ln * 16);
      uint32_t x[8];
      int budget = 1 << 18;
      do {
        spend(budget);
        TMARKV(warp == 0, 28, 1000);
        ld_v4(pp, x[0], x[1], x[2], x[3]);
        ld_v4(pp + 512, x[4], x[5], x[6], x[7]);
      } while (__any_sync(~0u, max(max(max(x[0], x[1]), max(x[2], x[3])), max(max(x[4], x[5]), max(x[6], x[7]))) == ~0u));
      sts128(ma + warp * 1024, x[0], x[1], x[2], x[3]);
      sts128(ma + warp * 1024 + 512, x[4], x[5], x[6], x[7]);
      fence_async_smem();
      bar_sync(NB_P, 256);
    }
    TMARKD(warp == 0, 14, 0);
    float d[16];
    if (R0) {
      if (s + 1 == kNSeg) break;
      const uint32_t unit = head * 4 + (warp >> 1), so = (s & 1) * 32768;
      const unsigned char* mb = g_mail + (unit * 8192 + (lds32(sb + TABS + unit * 4) & 4096u) + (warp & 1) * 32 + (ln >> 4) * 256 + (ln & 3) * 64 + ((ln >> 2) & 3) * 8);
      unsigned char* pwp = g_pub + ((unit >> 5) * 8192 + (unit & 31) * 64 + (warp & 1) * 32 + so + (ln & 1) * 4096 + (ln >> 2) * 4);
      const uint32_t sel = (ln & 4) ? 0x3F800000u : 0x3F80u;
      const uint32_t tagm = (s & 1) ? 0u : ~0u;
      bar_sync(NB_M, 288);
      spin_gt_until(lds32(sb + TK_X));
      TMARKD(warp == 0, 16, 0);
      for (int budget = 1 << 18;;) {
        uint32_t x[8];
#pragma unroll
        for (int i = 0; i < 4; i++) ld_v2(mb + i * 512, x[2 * i], x[2 * i + 1]);
        TMARKD(warp == 0, 15, x[0]);
        TMARKD(warp == 0, 23, x[0] | x[2] | x[4] | x[6]);
        float c[4], e[4];
        mma16z(c, x[0], x[1], x[2], x[3], sel, sel);
        mma16z(e, x[4], x[5], x[6], x[7], sel, sel);
        const bool ok = !__any_sync(~0u, (lop3<0x7e>(x[0], tagm, x[2]) | lop3<0x7e>(x[4], tagm, x[6])) & 1u);
#pragma unroll
        for (int i = 0; i < 4; i++) c[i] += e[i];
        const bool hi = ln & 16;
        const float u0 = (hi ? c[2] : c[0]) + __shfl_xor_sync(~0u, hi ? c[0] : c[2], 16);
        const float u1 = (hi ? c[3] : c[1]) + __shfl_xor_sync(~0u, hi ? c[1] : c[3], 16);
        const uint32_t wv = pack2(u0, u1);
        asm volatile("{.reg .pred p; setp.ne.u32 p, %2, 0; @p st.relaxed.gpu.global.u32 [%0], %1;}" ::"l"(pwp), "r"(wv), "r"((uint32_t)(ok && !(ln & 2))) : "memory");
        if (ok) { TMARKD(warp == 0, 9, wv); TMARKV(warp < 2, 24 + warp, (1 << 18) - budget); break; }
        spend(budget);
      }
      sts32(sb + TK + 16 + warp * 4, gtime());
      if (ln == 0) mbar_arrive(sb + B_PUB);
      if (!(ln & 2)) st_u32(pwp + (32768 - 2 * (int)so), ~0u);
      if (s + 2 == kNSeg) continue;
      mbar_wait(sb + B_XF + 8 * (s & 1), ((s + 2) >> 1) & 1);
      if (lds32(sb + TK_Q + (s & 1) * 4)) continue;
      mbar_wait(sb + B_PUB, s & 1);
      r_proj_issue(w, d, sb, s, warp, 0, 32);
    } else {
      if (s + 3 < kNSeg) mbar_wait(sb + B_XF + 8 * ((s + 1) & 1), ((s + 3) >> 1) & 1);
      if (kSplit) r_proj_issue(w, d, sb, s + 1, warp, 0, kSplit);
      uint32_t b[8];
      float c0[4], c1[4];
      const uint32_t va = sb + ln * 16 + (KV + 10240 + 8192) + (s & 3) * 20480 + (warp >> 2) * 1024;
      mbar_wait(sb + B_V, s & 1);
      ldsm4t(va, b[0], b[1], b[2], b[3]);
      ldsm4t(va + 512, b[4], b[5], b[6], b[7]);
      mma16z(c0, a3[0], a3[1], a3[2], a3[3], b[0], b[1]);
      mma16z(c1, a3[4], a3[5], a3[6], a3[7], b[2], b[3]);
      mma16(c0, a3[8], a3[9], a3[10], a3[11], b[4], b[5]);
      mma16(c1, a3[12], a3[13], a3[14], a3[15], b[6], b[7]);
      sts64(sb + ln * 16 + (VM + 4096) + (warp & 3) * 512 + (warp >> 2) * 8, pack2(c0[0] + c1[0], c0[1] + c1[1]), pack2(c0[2] + c1[2], c0[3] + c1[3]));
      bar_arrive(NB_S, 480);
      TMARKD(warp == 0, 18, 0);
      bar_sync(NB_TD, 384);
      TMARKD(warp == 1, 22, 0);
      r_proj_issue(w, d, sb, s + 1, warp, kSplit, 32);
    }
    wg_wait<0>();
    TMARKD(warp == 0, 7, __float_as_uint(d[0]));
    r_proj_store<R0>(d, sb, s + LA, warp, ln, rank);
    TMARKD(warp == 0, 2, 0);
  }
}

__global__ void __cluster_dims__(3, 1, 1) __launch_bounds__(512, 1)
recur_kernel(const __grid_constant__ CUtensorMap tmX, const __grid_constant__ CUtensorMap tmWq,
             const __grid_constant__ CUtensorMap tmWk, const __grid_constant__ CUtensorMap tmWv,
             const bf16* __restrict__ mem0, const bf16* __restrict__ Wo) {
  using namespace rk;
  extern __shared__ unsigned char smem_raw[];
  const uint32_t sb = (smem_u32(smem_raw) + 1023u) & ~1023u;
  const int warp = __shfl_sync(~0u, threadIdx.x >> 5, 0), lane = threadIdx.x & 31;
  const uint32_t rank = blockIdx.x % 3u, head = blockIdx.x / 3u;
  TSTAMP(threadIdx.x == 0, blockIdx.x * 80);
  asm volatile("griddepcontrol.launch_dependents;");

  if (threadIdx.x == 0) {
    for (int i = 0; i < 4; i++) { mbar_init(sb + B_KV + 8 * i, 1); mbar_init(sb + B_W + 8 * i, 1); }
    for (int i = 0; i < 4; i++) { mbar_init(sb + B_MEM + 8 * i, 1); mbar_init(sb + B_Q + 8 * i, 1); }
    mbar_init(sb + B_QK, rank == 2 ? 1 : 9);
    mbar_init(sb + B_V, rank == 2 ? 9 : 1);
    for (int i = 0; i < 2; i++) mbar_init(sb + B_XF + 8 * i, 1);
    mbar_init(sb + B_FREE, 24);
    mbar_init(sb + B_OF, 4);
    mbar_init(sb + B_PUB, rank == 0 ? 8 : 4);
    mbar_init(sb + B_OK, 1);
    for (int i = 0; i < 4; i++) mbar_init(sb + B_FIX + 8 * i, 1);
    asm volatile("fence.mbarrier_init.release.cluster;" ::: "memory");
    mbar_arrive_tx(sb + B_QK, rank == 2 ? 4096 : 2048);
    mbar_arrive_tx(sb + B_V, rank == 2 ? 0 : 2048);
    const CUtensorMap* tw = rank == 0 ? &tmWq : rank == 1 ? &tmWk : &tmWv;
    for (int c = 0; c < 4; c++) {
      mbar_arrive_tx(sb + B_W + 8 * c, 32768);
      for (int i = 0; i < 4; i++) {
        const int kb = 2 * c + (i >> 1), nb = i & 1;
        tma_2d(sb + RA + (kb * 2 + nb) * 8192, tw, head * 128 + nb * 64, kb * 64, sb + B_W + 8 * c);
      }
    }
    for (int st = 0; st < 2; st++) {
      mbar_arrive_tx(sb + B_XF + 8 * st, 32768);
      tma_3d(sb + XT + st * 32768, &tmX, 0, st * 32, 0, sb + B_XF + 8 * st);
    }
  }
  cluster_sync_all();

  if (warp < 8) {
    asm volatile("setmaxnreg.inc.sync.aligned.u32 160;");
    if (lane == 0) sts32(sb + TK_PG + warp * 4, near_page(g_pub + warp * 8192 + 2048 + blockIdx.x * 16));
    __syncwarp();
    bar_arrive(NB_TAB, 512);
    if (rank == 0) r_proj_role<true>(sb, warp, lane, rank, head, &tmX);
    else r_proj_role<false>(sb, warp, lane, rank, head, &tmX);
  } else if (warp < 12) {
    asm volatile("setmaxnreg.inc.sync.aligned.u32 136;");
    if (rank == 0) r_attn_role<2>(sb, warp - 8, lane, rank, head, Wo);
    else r_attn_role<3>(sb, warp - 8, lane, rank, head, Wo);
  } else {
    asm volatile("setmaxnreg.dec.sync.aligned.u32 56;");
    const int mw = warp - 12;
    const uint32_t unit = head * 4 + mw;
    const uint32_t pwo = (unit >> 5) * 8192 + (unit & 31) * 64;
    uint32_t mpage = 0;
    if (rank == 0) {
#pragma unroll
      for (int i = 0; i < 8; i++) st_b128(g_mail + unit * 8192 + (i >> 2) * 4096 + (i & 3) * 512 + lane * 16, 0u, 0u, 0u, 0u);
      st_v2(g_pub + pwo + (lane >> 4) * 32768 + ((lane >> 3) & 1) * 4096 + (lane & 7) * 8, ~0u, ~0u);
      if (lane == 0) mpage = near_page(g_mail + unit * 8192 + 2048);
      asm volatile("fence.acq_rel.gpu;" ::: "memory");
      mpage = __shfl_sync(~0u, mpage, 0);
      if (lane == 0) st_u32(&g_tab[unit], mpage | 1u);
    }
#pragma unroll
    for (int i = 0; i < 4; i++) {
      const int idx = mw * 128 + i * 32 + lane;
      const uint4 v = __ldg(reinterpret_cast<const uint4*>(mem0 + (idx & 7) * kD + (idx >> 3) * 8));
      sts128(sb + MEMS + idx * 16, v.x, v.y, v.z, v.w);
    }
    if (mw == 3 && lane < 16) sts32(sb + TK + lane * 4, lane < 14 ? gtime() : 0u);
    {
      uint32_t v;
      int budget = 1 << 20;
      while ((v = ld_u32(&g_tab[mw * 32 + lane])) == 0u) spend(budget);
      sts32(sb + TABS + (mw * 32 + lane) * 4, v);
      asm volatile("fence.acq_rel.gpu;" ::: "memory");
    }
    TSTAMP(mw == 0 && lane == 0, blockIdx.x * 80 + 4);
    bar_sync(NB_TAB, 512);
    TSTAMP(mw == 0 && lane == 0, blockIdx.x * 80 + 5);
    if (mw == 3) {
      if (lane < 4) mbar_arrive(sb + B_MEM + 8 * lane);
      r_timer_role(sb, lane, rank == 0);
    } else if (mw == 2) r_mscore_role(sb, lane, rank, head, &tmX);
    else r_score_role(sb, mw, lane, rank == 0 ? 224 : 480);
  }
  cluster_sync_all();
}

namespace gk {
constexpr int kCtas = 36, kStages = 4;
constexpr uint32_t STG = 49152;
constexpr uint32_t EPI = kStages * STG;
constexpr uint32_t BAR = EPI + 32768;
constexpr uint32_t INFO = BAR + 64;
constexpr uint32_t AUX = INFO + 16;
constexpr uint32_t SMEM = AUX + 64 + 1024;
constexpr int kQ = 240, kF1 = 224, kF2 = 32;
constexpr int kFirstSplit = 9;
__host__ __device__ constexpr int nsplit(int rb) { return rb < 9 ? 1 : rb < 12 ? 2 : rb < 14 ? 4 : rb == 14 ? 8 : 16; }
constexpr int kWo = 2 * (9 + 6 + 8 + 8 + 16);
constexpr int kUnits = kQ + kF1 + kF2 + kWo;
constexpr uint32_t kDraws = kUnits + kCtas;
constexpr int NB_EPI = 1, NB_DEP = 2;
}

__device__ __forceinline__ void wgmma_256(float (&d)[128], uint64_t adesc, uint64_t bdesc, int acc) {
  asm volatile("{.reg .pred p; setp.ne.b32 p, %130, 0;\n"
    "wgmma.mma_async.sync.aligned.m64n256k16.f32.bf16.bf16 {"
    "%0,%1,%2,%3,%4,%5,%6,%7,%8,%9,%10,%11,%12,%13,%14,%15,%16,%17,%18,%19,%20,%21,%22,%23,%24,%25,%26,%27,%28,%29,%30,%31,"
    "%32,%33,%34,%35,%36,%37,%38,%39,%40,%41,%42,%43,%44,%45,%46,%47,%48,%49,%50,%51,%52,%53,%54,%55,%56,%57,%58,%59,%60,%61,%62,%63,"
    "%64,%65,%66,%67,%68,%69,%70,%71,%72,%73,%74,%75,%76,%77,%78,%79,%80,%81,%82,%83,%84,%85,%86,%87,%88,%89,%90,%91,%92,%93,%94,%95,"
    "%96,%97,%98,%99,%100,%101,%102,%103,%104,%105,%106,%107,%108,%109,%110,%111,%112,%113,%114,%115,%116,%117,%118,%119,%120,%121,%122,%123,%124,%125,%126,%127"
    "}, %128, %129, p, 1, 1, 0, 1;}"
#define D8(i) "+f"(d[i]), "+f"(d[i + 1]), "+f"(d[i + 2]), "+f"(d[i + 3]), "+f"(d[i + 4]), "+f"(d[i + 5]), "+f"(d[i + 6]), "+f"(d[i + 7])
    : D8(0), D8(8), D8(16), D8(24), D8(32), D8(40), D8(48), D8(56), D8(64), D8(72), D8(80), D8(88), D8(96), D8(104), D8(112), D8(120)
#undef D8
    : "l"(adesc), "l"(bdesc), "r"(acc));
}
__device__ __forceinline__ void wait_count(const unsigned* p, uint32_t target, int& budget) {
  while ((int)(ld_acq(p) - target) < 0) { spend(budget); __nanosleep(64); }
}
__device__ __forceinline__ float sigmoidf_(float x) { float t; asm("tanh.approx.f32 %0, %1;" : "=f"(t) : "f"(0.5f * x)); return fmaf(t, 0.5f, 0.5f); }
__device__ __forceinline__ uint32_t add_bf2(uint32_t a, uint32_t b) { uint32_t r; asm("add.rn.bf16x2 %0, %1, %2;" : "=r"(r) : "r"(a), "r"(b)); return r; }

template <bool ADD>
__device__ __forceinline__ void g_store_out(const float (&d)[128], float s0, float s1, uint32_t stg, bf16* __restrict__ dst, int lane) {
  const uint32_t wa = stg + (lane & 15) * 256, wx = (lane >> 4) ^ (lane & 7);
#pragma unroll
  for (int h = 0; h < 2; h++) {
    uint4 prev[8];
    if (ADD) {
#pragma unroll
      for (int i = 0; i < 8; i++) prev[i] = __ldcg(reinterpret_cast<const uint4*>(dst + (2 * i + (lane >> 4)) * kD + h * 128 + (lane & 15) * 8));
    }
#pragma unroll
    for (int i = 0; i < 8; i++) {
      const float* p = d + 64 * h + 8 * i;
      stsm4(wa + (((2 * i) ^ wx) << 4), pack2(p[0] * s0, p[1] * s0), pack2(p[2] * s1, p[3] * s1), pack2(p[4] * s0, p[5] * s0), pack2(p[6] * s1, p[7] * s1));
    }
    __syncwarp();
#pragma unroll
    for (int i = 0; i < 8; i++) {
      const int row = 2 * i + (lane >> 4);
      uint4 v;
      lds128(stg + row * 256 + (((lane & 15) ^ (row & 7)) << 4), v.x, v.y, v.z, v.w);
      if (ADD) { v.x = add_bf2(v.x, prev[i].x); v.y = add_bf2(v.y, prev[i].y); v.z = add_bf2(v.z, prev[i].z); v.w = add_bf2(v.w, prev[i].w); }
      *reinterpret_cast<uint4*>(dst + row * kD + h * 128 + (lane & 15) * 8) = v;
    }
    __syncwarp();
  }
}

__global__ void __launch_bounds__(384, 1)
gemm_kernel(const __grid_constant__ CUtensorMap tmX, const __grid_constant__ CUtensorMap tmWg, const __grid_constant__ CUtensorMap tmWu,
            const __grid_constant__ CUtensorMap tmWd, const __grid_constant__ CUtensorMap tmWo, const __grid_constant__ CUtensorMap tmWq,
            const bf16* __restrict__ x, const bf16* __restrict__ gw, bf16* __restrict__ out) {
  using namespace gk;
  extern __shared__ unsigned char smem_raw[];
  const uint32_t sb = (smem_u32(smem_raw) + 1023u) & ~1023u;
  const int warp = __shfl_sync(~0u, threadIdx.x >> 5, 0), lane = threadIdx.x & 31;
  int budget = 1 << 20;
  TSTAMP(threadIdx.x == 0, (96 + blockIdx.x) * 80);
  if (threadIdx.x == 0) {
    for (int i = 0; i < kStages; i++) { mbar_init(sb + BAR + 8 * i, 1); mbar_init(sb + BAR + 32 + 8 * i, 2); }
    asm volatile("fence.mbarrier_init.release.cluster;" ::: "memory");
  }
  __syncthreads();

  if (warp < 4) {
    asm volatile("setmaxnreg.dec.sync.aligned.u32 40;");
    if (warp == 0) {
      if (lane == 0) {
        uint32_t it = 0;
        while (true) {
          const uint32_t tk = atomicAdd(&g_ticket, 1u);
          const uint32_t ep = tk / kDraws + 1;
          int u = (int)(tk % kDraws) - kQ, type, rb, nb, piece = 0, k0 = 0, nk;
          if (u < 0) { type = 4; rb = 16 + (u >> 4); nb = u & 15; nk = 8; }
          else if (u < kF1) { type = 0; rb = u / 14; nb = u % 14; nk = 8; }
          else if (u < kF1 + kF2) { type = 1; rb = (u - kF1) >> 1; nb = u & 1; nk = 28; }
          else if (u < kUnits - kQ) {
            type = 2; u -= kF1 + kF2; rb = 0;
            while (u >= 2 * nsplit(rb)) { u -= 2 * nsplit(rb); rb++; }
            nb = u & 1; piece = u >> 1; nk = 64 / nsplit(rb); k0 = piece * nk;
          } else { type = 3; rb = nb = 0; nk = 1; }
          const uint32_t code = type | rb << 3 | nb << 7;
          if (it == 0) sts32(sb + AUX + 4, ep);
          const bf16* asrc = type == 1 ? g_hid + (size_t)rb * 28 * 8192 : g_o + (size_t)(rb * 64 + k0) * 8192;
          const int pre = type == 0 ? 0 : nk < kStages ? nk : kStages;
          for (int k = 0; k < nk; k++) {
            const uint32_t st = (it + k) % kStages, ph = ((it + k) / kStages) & 1;
            const uint32_t full = sb + BAR + 8 * st, sa = sb + st * STG;
            mbar_wait(full + 32, ph ^ 1, budget);
            asm volatile("st.shared.u32 [%0], %1;" ::"r"(sb + INFO + 4 * st), "r"(code) : "memory");
            if (type == 3) { mbar_arrive(full); break; }
            mbar_arrive_tx(full, STG);
            if (type == 0) {
              tma_2d(sa, &tmX, k * 64, rb * 128, full);
              tma_3d(sa + 16384, &tmWg, 0, k * 64, nb * 2, full);
              tma_3d(sa + 32768, &tmWu, 0, k * 64, nb * 2, full);
            } else if (type == 4) {
              tma_2d(sa, &tmX, k * 64, rb * 128, full);
              tma_3d(sa + 16384, &tmWq, 0, k * 64, nb * 4, full);
            } else {
              tma_3d(sa + 16384, type == 1 ? &tmWd : &tmWo, 0, (k0 + k) * 64, nb * 4, full);
              if (k >= pre) bulk_g2s(sa, asrc + k * 8192, 16384, full);
              else if (k == pre - 1) {
                if (type == 1) wait_count(&g_cnt[C_HID + rb], ep * 16, budget);
                else wait_count(&g_cnt[C_O + rb], ep * 128, budget);
                asm volatile("fence.proxy.async.global;" ::: "memory");
                for (int j = 0; j < pre; j++) bulk_g2s(sb + ((it + j) % kStages) * STG, asrc + j * 8192, 16384, sb + BAR + 8 * ((it + j) % kStages));
              }
            }
          }
          if (type == 3) break;
          it += nk;
        }
      }
    } else if (warp == 1) {
      while (true) {
        bar_sync(NB_EPI, 288);
        uint32_t idx;
        asm volatile("ld.shared.u32 %0, [%1];" : "=r"(idx) : "r"(sb + AUX) : "memory");
        bar_arrive(NB_DEP, 288);
        if (idx == ~0u) break;
        if (lane == 0) asm volatile("fence.proxy.async.global; red.release.gpu.global.add.u32 [%0], 1;" ::"l"(&g_cnt[idx]) : "memory");
      }
    } else if (blockIdx.x < 16) {
      float w[16];
#pragma unroll
      for (int i = 0; i < 2; i++) {
        const uint4 v = __ldg(reinterpret_cast<const uint4*>(gw + i * 256 + lane * 8));
        const uint32_t q[4] = {v.x, v.y, v.z, v.w};
#pragma unroll
        for (int j = 0; j < 4; j++) { w[8 * i + 2 * j] = __uint_as_float(q[j] << 16); w[8 * i + 2 * j + 1] = __uint_as_float(q[j] & 0xffff0000u); }
      }
      const int r0 = blockIdx.x * 128 + (warp - 2) * 64;
      for (int r = r0; r < r0 + 64; r++) {
        float a = 0.f;
#pragma unroll
        for (int i = 0; i < 2; i++) {
          const uint4 v = __ldg(reinterpret_cast<const uint4*>(x + r * kD + i * 256 + lane * 8));
          const uint32_t q[4] = {v.x, v.y, v.z, v.w};
#pragma unroll
          for (int j = 0; j < 4; j++) a = fmaf(__uint_as_float(q[j] << 16), w[8 * i + 2 * j], fmaf(__uint_as_float(q[j] & 0xffff0000u), w[8 * i + 2 * j + 1], a));
        }
#pragma unroll
        for (int o = 16; o; o >>= 1) a += __shfl_xor_sync(~0u, a, o);
        if (lane == 0) g_gate[r] = 1.f / (1.f + __expf(-a));
      }
      if (lane == 0) asm volatile("red.release.gpu.global.add.u32 [%0], 1;" ::"l"(&g_cnt[C_HID + blockIdx.x]) : "memory");
    }
  } else {
    asm volatile("setmaxnreg.inc.sync.aligned.u32 232;");
    const int cw = warp - 4, ct = threadIdx.x - 128;
    const uint32_t stg = sb + EPI + cw * 4096;
    uint32_t it = 0;
    bool pending = false;
    float d[128];
    while (true) {
      mbar_wait(sb + BAR + 8 * (it % kStages), (it / kStages) & 1, budget);
      uint32_t code;
      asm volatile("ld.shared.u32 %0, [%1];" : "=r"(code) : "r"(sb + INFO + 4 * (it % kStages)) : "memory");
      const int type = code & 7, rb = (code >> 3) & 15, nb = code >> 7;
      const uint32_t ep = lds32(sb + AUX + 4);
      if (type == 3) break;
      TSTAMP(ct == 0, (96 + blockIdx.x) * 80 + 8 + 4 * rb + min(type, 3));
      const int nk = type == 1 ? 28 : type == 2 ? 64 / nsplit(rb) : 8;
      for (int k = 0; k < nk; k++, it++) {
        const uint32_t st = it % kStages;
        if (k) mbar_wait(sb + BAR + 8 * st, (it / kStages) & 1, budget);
        const uint64_t ad = make_desc(sb + st * STG + (cw >> 2) * 8192, 16, 1024, 1);
        const uint64_t bd = make_desc(sb + st * STG + 16384, 8192, 1024, 1);
        wg_fence();
#pragma unroll
        for (int j = 0; j < 4; j++) wgmma_256(d, ad + (uint64_t)(2 * j), bd + (uint64_t)(128 * j), k | j);
        wg_commit();
        wg_wait<1>();
        if (k && (ct & 127) == 0) mbar_arrive(sb + BAR + 32 + 8 * ((it - 1) % kStages));
      }
      wg_wait<0>();
      if ((ct & 127) == 0) mbar_arrive(sb + BAR + 32 + 8 * ((it - 1) % kStages));
      const int row = rb * 128 + cw * 16;
      uint32_t flag = ~1u;
      if (type == 0) {
        const uint32_t wa = stg + (lane & 15) * 128, wx = (lane >> 4) ^ (lane & 7);
#pragma unroll
        for (int i = 0; i < 8; i++) {
          float h[8];
#pragma unroll
          for (int j = 0; j < 8; j++) h[j] = sigmoidf_(d[8 * i + j]) * d[64 + 8 * i + j];
          stsm4(wa + (i >> 2) * 2048 + (((2 * (i & 3)) ^ wx) << 4), pack2(h[0], h[1]), pack2(h[2], h[3]), pack2(h[4], h[5]), pack2(h[6], h[7]));
        }
        __syncwarp();
        bf16* dst = g_hid + (size_t)(rb * 28 + nb * 2) * 8192 + cw * 1024 + lane * 8;
#pragma unroll
        for (int i = 0; i < 8; i++) {
          uint4 v;
          lds128(stg + i * 512 + lane * 16, v.x, v.y, v.z, v.w);
          *reinterpret_cast<uint4*>(dst + (i >> 2) * 8192 + (i & 3) * 256) = v;
        }
        __syncwarp();
        flag = C_HID + rb;
      } else if (type == 4) {
        const uint32_t wa = stg + (lane & 15) * 128, wx = (lane >> 4) ^ (lane & 7);
#pragma unroll
        for (int h = 0; h < 2; h++) {
#pragma unroll
          for (int i = 0; i < 8; i++) {
            const float* p = d + 64 * h + 8 * i;
            stsm4(wa + (i >> 2) * 2048 + (((2 * (i & 3)) ^ wx) << 4), pack2(p[0], p[1]), pack2(p[2], p[3]), pack2(p[4], p[5]), pack2(p[6], p[7]));
          }
          __syncwarp();
          bf16* dst = g_q + (size_t)(rb * 64 + nb * 4 + h * 2) * 8192 + cw * 1024 + lane * 8;
#pragma unroll
          for (int i = 0; i < 8; i++) {
            uint4 v;
            lds128(stg + i * 512 + lane * 16, v.x, v.y, v.z, v.w);
            *reinterpret_cast<uint4*>(dst + (i >> 2) * 8192 + (i & 3) * 256) = v;
          }
          __syncwarp();
        }
        flag = C_Q + rb * 16 + nb;
      } else {
        const int tile = rb * 2 + nb;
        float4* acc = reinterpret_cast<float4*>(g_acc) + (size_t)(tile - 2 * kFirstSplit) * 8192 + ct;
        bf16* dst = out + row * kD + nb * 256;
        if (type == 2) {
          if (lane == 0) wait_count(&g_cnt[C_F2 + tile], ep, budget);
          __syncwarp();
        }
        const float g0 = __ldcg(&g_gate[row + (lane >> 2)]), g1 = __ldcg(&g_gate[row + 8 + (lane >> 2)]);
        if (type == 1) {
          const float s0 = 1.f - g0, s1 = 1.f - g1;
          if (rb < kFirstSplit) g_store_out<false>(d, s0, s1, stg, dst, lane);
          else {
#pragma unroll
            for (int i = 0; i < 32; i++) acc[i * 256] = make_float4(d[4 * i] * s0, d[4 * i + 1] * s0, d[4 * i + 2] * s1, d[4 * i + 3] * s1);
          }
          flag = C_F2 + tile;
        } else if (rb < kFirstSplit) {
          g_store_out<true>(d, g0, g1, stg, dst, lane);
        } else {
          const uint32_t ns = nsplit(rb);
          uint32_t tk = 0;
          if (lane == 0) tk = atomicAdd(&g_cnt[C_ARR + tile * 8 + cw], 1u);
          tk = __shfl_sync(~0u, tk, 0);
          if (tk != ep * ns - 1) {
#pragma unroll
            for (int i = 0; i < 32; i++)
              asm volatile("red.relaxed.gpu.global.add.v4.f32 [%0], {%1,%2,%3,%4};" ::"l"(acc + i * 256), "f"(d[4 * i] * g0), "f"(d[4 * i + 1] * g0),
                           "f"(d[4 * i + 2] * g1), "f"(d[4 * i + 3] * g1) : "memory");
            __syncwarp();
            if (lane == 0) asm volatile("red.release.gpu.global.add.u32 [%0], 1;" ::"l"(&g_cnt[C_DONE + tile * 8 + cw]) : "memory");
          } else {
            if (lane == 0) wait_count(&g_cnt[C_DONE + tile * 8 + cw], ep * (ns - 1), budget);
            __syncwarp();
#pragma unroll
            for (int i = 0; i < 32; i++) {
              const float4 v = __ldcg(acc + i * 256);
              d[4 * i] = fmaf(d[4 * i], g0, v.x); d[4 * i + 1] = fmaf(d[4 * i + 1], g0, v.y);
              d[4 * i + 2] = fmaf(d[4 * i + 2], g1, v.z); d[4 * i + 3] = fmaf(d[4 * i + 3], g1, v.w);
            }
            g_store_out<false>(d, 1.f, 1.f, stg, dst, lane);
          }
        }
      }
      if (flag != ~1u) {
        if (pending) bar_sync(NB_DEP, 288);
        if (ct == 0) asm volatile("st.shared.u32 [%0], %1;" ::"r"(sb + AUX), "r"(flag) : "memory");
        bar_arrive(NB_EPI, 288);
        pending = true;
      }
    }
    TSTAMP(ct == 0, (96 + blockIdx.x) * 80 + 1);
    if (pending) bar_sync(NB_DEP, 288);
    if (ct == 0) asm volatile("st.shared.u32 [%0], %1;" ::"r"(sb + AUX), "r"(~0u) : "memory");
    bar_arrive(NB_EPI, 288);
    bar_sync(NB_DEP, 288);
  }
}

typedef CUresult (*EncodeFn)(CUtensorMap*, CUtensorMapDataType, cuuint32_t, void*, const cuuint64_t*, const cuuint64_t*,
                             const cuuint32_t*, const cuuint32_t*, CUtensorMapInterleave, CUtensorMapSwizzle,
                             CUtensorMapL2promotion, CUtensorMapFloatOOBfill);

static void make_map(EncodeFn fn, CUtensorMap* m, const void* base, uint64_t cols, uint64_t rows, uint32_t bc, uint32_t br) {
  cuuint64_t dims[2] = {cols, rows};
  cuuint64_t strides[1] = {cols * 2};
  cuuint32_t box[2] = {bc, br};
  cuuint32_t es[2] = {1, 1};
  fn(m, CU_TENSOR_MAP_DATA_TYPE_BFLOAT16, 2, const_cast<void*>(base), dims, strides, box, es, CU_TENSOR_MAP_INTERLEAVE_NONE,
     CU_TENSOR_MAP_SWIZZLE_128B, CU_TENSOR_MAP_L2_PROMOTION_L2_256B, CU_TENSOR_MAP_FLOAT_OOB_FILL_NONE);
}

static void make_map3(EncodeFn fn, CUtensorMap* m, const void* base, uint64_t cols, uint64_t rows, uint32_t br, uint32_t nc) {
  cuuint64_t dims[3] = {64, rows, cols / 64};
  cuuint64_t strides[2] = {cols * 2, 128};
  cuuint32_t box[3] = {64, br, nc};
  cuuint32_t es[3] = {1, 1, 1};
  fn(m, CU_TENSOR_MAP_DATA_TYPE_BFLOAT16, 3, const_cast<void*>(base), dims, strides, box, es, CU_TENSOR_MAP_INTERLEAVE_NONE,
     CU_TENSOR_MAP_SWIZZLE_128B, CU_TENSOR_MAP_L2_PROMOTION_L2_256B, CU_TENSOR_MAP_FLOAT_OOB_FILL_NONE);
}

extern "C" void kernel_launch(void* const* d_in, const int* in_sizes, int n_in, void* d_out, int out_size) {
  const bf16* x = (const bf16*)d_in[0];
  const bf16* mem0 = (const bf16*)d_in[1];
  const bf16* Wo = (const bf16*)d_in[5];
  void* fp = nullptr;
  cudaDriverEntryPointQueryResult qr;
  cudaGetDriverEntryPoint("cuTensorMapEncodeTiled", &fp, cudaEnableDefault, &qr);
  EncodeFn fn = (EncodeFn)fp;
  CUtensorMap tmX, tmWq, tmWk, tmWv;
  make_map3(fn, &tmX, x, kD, kS, 32, 8);
  make_map(fn, &tmWq, d_in[2], 4096, kD, 64, 64);
  make_map(fn, &tmWk, d_in[3], 4096, kD, 64, 64);
  make_map(fn, &tmWv, d_in[4], 4096, kD, 64, 64);
  cudaFuncSetAttribute(recur_kernel, cudaFuncAttributeMaxDynamicSharedMemorySize, rk::SMEM);
  recur_kernel<<<96, 512, rk::SMEM>>>(tmX, tmWq, tmWk, tmWv, mem0, Wo);
  CUtensorMap tmX2, tmWg, tmWu, tmWd, tmWo, tmWq2;
  make_map(fn, &tmX2, x, kD, kS, 64, 128);
  make_map3(fn, &tmWg, d_in[8], kF, kD, 64, 2);
  make_map3(fn, &tmWu, d_in[9], kF, kD, 64, 2);
  make_map3(fn, &tmWd, d_in[10], kD, kF, 64, 4);
  make_map3(fn, &tmWo, Wo, kD, 4096, 64, 4);
  make_map3(fn, &tmWq2, d_in[2], 4096, kD, 64, 4);
  cudaFuncSetAttribute(gemm_kernel, cudaFuncAttributeMaxDynamicSharedMemorySize, gk::SMEM);
  cudaLaunchConfig_t cfg = {};
  cfg.gridDim = dim3(gk::kCtas);
  cfg.blockDim = dim3(384);
  cfg.dynamicSmemBytes = gk::SMEM;
  cfg.stream = cudaStreamPerThread;
  cudaLaunchAttribute at[1];
  at[0].id = cudaLaunchAttributeProgrammaticStreamSerialization;
  at[0].val.programmaticStreamSerializationAllowed = 1;
  cfg.attrs = at;
  cfg.numAttrs = 1;
  cudaLaunchKernelEx(&cfg, gemm_kernel, tmX2, tmWg, tmWu, tmWd, tmWo, tmWq2, x, (const bf16*)d_in[11], (bf16*)d_out);
}
```

```cpp
#include <cuda_runtime.h>
#include <cuda_bf16.h>
#include <cuda.h>
#include <stdint.h>

typedef __nv_bfloat16 bf16;

constexpr int kS = 2048, kD = 512, kH = 32, kF = 1792, kNSeg = 64;

__device__ __align__(2097152) unsigned char g_mail[136 * 8192];
#define g_pub (g_mail + 128 * 8192)
__device__ __align__(16) unsigned g_tab[64];
__device__ __align__(1024) bf16 g_o[(size_t)kS * 4096];
__device__ __align__(1024) bf16 g_q[(size_t)kS * 4096];
__device__ __align__(1024) bf16 g_hid[kS * kF];
#define S0 36
constexpr int kS0 = S0;
__device__ __align__(16) uint32_t g_part[(size_t)(64 - kS0) * 65536];
__device__ float g_gate[kS];
__device__ unsigned g_ticket;
constexpr int C_HID = 0, C_O = 16, C_F2 = 32, C_S = 64, C_G = 320, C_Q = 576;
__device__ unsigned g_cnt[832];

#define TMARKD(cond, ev, dep)
#define TMARKV(cond, ev, v)
#define TSTAMP(cond, i)
#define TMARKW(set, ev, dep)
#define OPAQUE(v_) v_ = __shfl_xor_sync(~0u, v_, 0)

__device__ __forceinline__ uint32_t smem_u32(const void* p) { return (uint32_t)__cvta_generic_to_shared(p); }
__device__ __forceinline__ void mbar_init(uint32_t a, uint32_t n) { asm volatile("mbarrier.init.shared::cta.b64 [%0], %1;" ::"r"(a), "r"(n) : "memory"); }
__device__ __forceinline__ void mbar_arrive(uint32_t a) { asm volatile("mbarrier.arrive.shared::cta.b64 _, [%0];" ::"r"(a) : "memory"); }
__device__ __forceinline__ void mbar_arrive_tx(uint32_t a, uint32_t b) { asm volatile("mbarrier.arrive.expect_tx.shared::cta.b64 _, [%0], %1;" ::"r"(a), "r"(b) : "memory"); }
__device__ __forceinline__ void mbar_arrive_remote(uint32_t a) { asm volatile("mbarrier.arrive.release.cluster.shared::cluster.b64 _, [%0];" ::"r"(a) : "memory"); }
__device__ __forceinline__ bool mbar_try(uint32_t a, uint32_t par) {
  uint32_t ok;
  asm volatile("{.reg .pred p; mbarrier.try_wait.parity.shared::cta.b64 p, [%1], %2; selp.u32 %0, 1, 0, p;}" : "=r"(ok) : "r"(a), "r"(par) : "memory");
  return ok;
}
__device__ __forceinline__ bool mbar_try_cl(uint32_t a, uint32_t par) {
  uint32_t ok;
  asm volatile("{.reg .pred p; mbarrier.try_wait.parity.acquire.cluster.shared::cta.b64 p, [%1], %2; selp.u32 %0, 1, 0, p;}" : "=r"(ok) : "r"(a), "r"(par) : "memory");
  return ok;
}
__device__ __forceinline__ void spend(int& budget) { asm volatile("{.reg .pred p; .reg .u64 z; mov.u64 z, 0; add.s32 %0, %0, -1; setp.lt.s32 p, %0, 0; @p st.global.u32 [z], %0;}" : "+r"(budget)); }
__device__ __forceinline__ void mbar_wait(uint32_t a, uint32_t par, int& budget) { while (!mbar_try(a, par)) { spend(budget); } }
__device__ __forceinline__ void mbar_wait(uint32_t a, uint32_t par) {
  if (!mbar_try(a, par)) { int budget = 1 << 18; do { spend(budget); } while (!mbar_try(a, par)); }
}
__device__ __forceinline__ void mbar_wait_cl(uint32_t a, uint32_t par) { int budget = 1 << 18; while (!mbar_try_cl(a, par)) { spend(budget); } }
__device__ __forceinline__ uint32_t mapa(uint32_t a, uint32_t r) { uint32_t o; asm("mapa.shared::cluster.u32 %0, %1, %2;" : "=r"(o) : "r"(a), "r"(r)); return o; }
__device__ __forceinline__ void fence_async_smem() { asm volatile("fence.proxy.async.shared::cta;" ::: "memory"); }
__device__ __forceinline__ void bar_sync(int id, int n) { asm volatile("bar.sync %0, %1;" ::"r"(id), "r"(n) : "memory"); }
__device__ __forceinline__ void bar_sync_after(int id, int n, uint32_t dep, uint32_t skip) {
  asm volatile("{.reg .pred p; setp.eq.u32 p, %2, 0; @p bar.sync %0, %1;}" ::"r"(id), "r"(n), "r"((dep & blockIdx.y) | skip) : "memory");
}
__device__ __forceinline__ bool bar_red_or(int id, int n, bool v) {
  uint32_t r;
  asm volatile("{.reg .pred p, q; setp.ne.u32 q, %3, 0; bar.red.or.pred p, %1, %2, q; selp.u32 %0, 1, 0, p;}" : "=r"(r) : "r"(id), "r"(n), "r"((uint32_t)v) : "memory");
  return r;
}
__device__ __forceinline__ void bar_arrive(int id, int n) { asm volatile("bar.arrive %0, %1;" ::"r"(id), "r"(n) : "memory"); }
__device__ __forceinline__ void cluster_sync_all() {
  asm volatile("barrier.cluster.arrive.release.aligned; barrier.cluster.wait.acquire.aligned;" ::: "memory");
}
__device__ __forceinline__ void cluster_wait() { asm volatile("barrier.cluster.wait.acquire.aligned;" ::: "memory"); }
__device__ __forceinline__ void tma_2d(uint32_t dst, const CUtensorMap* tm, int c0, int c1, uint32_t bar) {
  asm volatile("cp.async.bulk.tensor.2d.shared::cluster.global.mbarrier::complete_tx::bytes [%0], [%1, {%3, %4}], [%2];"
               ::"r"(dst), "l"(tm), "r"(bar), "r"(c0), "r"(c1) : "memory");
}
__device__ __forceinline__ void tma_3d(uint32_t dst, const CUtensorMap* tm, int c0, int c1, int c2, uint32_t bar) {
  asm volatile("cp.async.bulk.tensor.3d.shared::cluster.global.mbarrier::complete_tx::bytes [%0], [%1, {%3, %4, %5}], [%2];"
               ::"r"(dst), "l"(tm), "r"(bar), "r"(c0), "r"(c1), "r"(c2) : "memory");
}
__device__ __forceinline__ void bulk_s2c(uint32_t dst, uint32_t src, uint32_t bytes, uint32_t bar) {
  asm volatile("cp.async.bulk.shared::cluster.shared::cta.mbarrier::complete_tx::bytes [%0], [%1], %2, [%3];"
               ::"r"(dst), "r"(src), "r"(bytes), "r"(bar) : "memory");
}
__device__ __forceinline__ void bulk_g2s(uint32_t dst, const void* src, uint32_t bytes, uint32_t bar) {
  asm volatile("cp.async.bulk.shared::cluster.global.mbarrier::complete_tx::bytes [%0], [%1], %2, [%3];" ::"r"(dst), "l"(src), "r"(bytes), "r"(bar) : "memory");
}
__device__ __forceinline__ void bulk_s2g(void* dst, uint32_t src, uint32_t bytes) {
  asm volatile("cp.async.bulk.global.shared::cta.bulk_group [%0], [%1], %2;" ::"l"(dst), "r"(src), "r"(bytes) : "memory");
}
__device__ __forceinline__ void st_async32(uint32_t dst, uint32_t v, uint32_t bar) {
  asm volatile("st.async.weak.shared::cluster.mbarrier::complete_tx::bytes.b32 [%0], %1, [%2];" ::"r"(dst), "r"(v), "r"(bar) : "memory");
}
__device__ __forceinline__ void ldsm4(uint32_t a, uint32_t& r0, uint32_t& r1, uint32_t& r2, uint32_t& r3) {
  asm volatile("ldmatrix.sync.aligned.m8n8.x4.shared.b16 {%0,%1,%2,%3}, [%4];" : "=r"(r0), "=r"(r1), "=r"(r2), "=r"(r3) : "r"(a) : "memory");
}
__device__ __forceinline__ void ldsm4t(uint32_t a, uint32_t& r0, uint32_t& r1, uint32_t& r2, uint32_t& r3) {
  asm volatile("ldmatrix.sync.aligned.m8n8.x4.trans.shared.b16 {%0,%1,%2,%3}, [%4];" : "=r"(r0), "=r"(r1), "=r"(r2), "=r"(r3) : "r"(a) : "memory");
}
__device__ __forceinline__ void ldsm2t(uint32_t a, uint32_t& r0, uint32_t& r1) {
  asm volatile("ldmatrix.sync.aligned.m8n8.x2.trans.shared.b16 {%0,%1}, [%2];" : "=r"(r0), "=r"(r1) : "r"(a) : "memory");
}
__device__ __forceinline__ void stsm4(uint32_t a, uint32_t r0, uint32_t r1, uint32_t r2, uint32_t r3) {
  asm volatile("stmatrix.sync.aligned.m8n8.x4.shared.b16 [%0], {%1,%2,%3,%4};" ::"r"(a), "r"(r0), "r"(r1), "r"(r2), "r"(r3) : "memory");
}
__device__ __forceinline__ void stsm2(uint32_t a, uint32_t r0, uint32_t r1) {
  asm volatile("stmatrix.sync.aligned.m8n8.x2.shared.b16 [%0], {%1,%2};" ::"r"(a), "r"(r0), "r"(r1) : "memory");
}
__device__ __forceinline__ void stsm4t(uint32_t a, uint32_t r0, uint32_t r1, uint32_t r2, uint32_t r3) {
  asm volatile("stmatrix.sync.aligned.m8n8.x4.trans.shared.b16 [%0], {%1,%2,%3,%4};" ::"r"(a), "r"(r0), "r"(r1), "r"(r2), "r"(r3) : "memory");
}
__device__ __forceinline__ void stsm1t(uint32_t a, uint32_t r0) {
  asm volatile("stmatrix.sync.aligned.m8n8.x1.trans.shared.b16 [%0], {%1};" ::"r"(a), "r"(r0) : "memory");
}
__device__ __forceinline__ void mma16z(float (&c)[4], uint32_t a0, uint32_t a1, uint32_t a2, uint32_t a3, uint32_t b0, uint32_t b1) {
  asm volatile("mma.sync.aligned.m16n8k16.row.col.f32.bf16.bf16.f32 {%0,%1,%2,%3}, {%4,%5,%6,%7}, {%8,%9}, {%10,%10,%10,%10};"
               : "=f"(c[0]), "=f"(c[1]), "=f"(c[2]), "=f"(c[3]) : "r"(a0), "r"(a1), "r"(a2), "r"(a3), "r"(b0), "r"(b1), "f"(0.f));
}
__device__ __forceinline__ void mma16(float (&c)[4], uint32_t a0, uint32_t a1, uint32_t a2, uint32_t a3, uint32_t b0, uint32_t b1) {
  asm volatile("mma.sync.aligned.m16n8k16.row.col.f32.bf16.bf16.f32 {%0,%1,%2,%3}, {%4,%5,%6,%7}, {%8,%9}, {%0,%1,%2,%3};"
               : "+f"(c[0]), "+f"(c[1]), "+f"(c[2]), "+f"(c[3]) : "r"(a0), "r"(a1), "r"(a2), "r"(a3), "r"(b0), "r"(b1));
}
__device__ __forceinline__ void mma8(float (&c)[4], uint32_t a0, uint32_t a1, uint32_t b0) {
  asm volatile("mma.sync.aligned.m16n8k8.row.col.f32.bf16.bf16.f32 {%0,%1,%2,%3}, {%4,%5}, {%6}, {%0,%1,%2,%3};"
               : "+f"(c[0]), "+f"(c[1]), "+f"(c[2]), "+f"(c[3]) : "r"(a0), "r"(a1), "r"(b0));
}
__device__ __forceinline__ void mma8z(float (&c)[4], uint32_t a0, uint32_t a1, uint32_t b0) {
  asm volatile("mma.sync.aligned.m16n8k8.row.col.f32.bf16.bf16.f32 {%0,%1,%2,%3}, {%4,%5}, {%6}, {%7,%7,%7,%7};"
               : "=f"(c[0]), "=f"(c[1]), "=f"(c[2]), "=f"(c[3]) : "r"(a0), "r"(a1), "r"(b0), "f"(0.f));
}
__device__ __forceinline__ uint32_t pack2(float lo, float hi) {
  uint32_t r; asm("cvt.rn.bf16x2.f32 %0, %1, %2;" : "=r"(r) : "f"(hi), "f"(lo)); return r;
}
__device__ __forceinline__ float ex2(float x) { float r; asm("ex2.approx.ftz.f32 %0, %1;" : "=f"(r) : "f"(x)); return r; }
__device__ __forceinline__ void wg_fence() { asm volatile("wgmma.fence.sync.aligned;" ::: "memory"); }
__device__ __forceinline__ void wg_commit() { asm volatile("wgmma.commit_group.sync.aligned;" ::: "memory"); }
template <int N> __device__ __forceinline__ void wg_wait() { asm volatile("wgmma.wait_group.sync.aligned %0;" ::"n"(N) : "memory"); }
template <int TB>
__device__ __forceinline__ void wgmma_rs32(float (&d)[16], uint32_t a0, uint32_t a1, uint32_t a2, uint32_t a3, uint64_t desc, int acc) {
  asm volatile("{.reg .pred p; setp.ne.b32 p, %21, 0;\n"
               "wgmma.mma_async.sync.aligned.m64n32k16.f32.bf16.bf16 {%0,%1,%2,%3,%4,%5,%6,%7,%8,%9,%10,%11,%12,%13,%14,%15}, {%16,%17,%18,%19}, %20, p, 1, 1, %22;}"
               : "+f"(d[0]), "+f"(d[1]), "+f"(d[2]), "+f"(d[3]), "+f"(d[4]), "+f"(d[5]), "+f"(d[6]), "+f"(d[7]),
                 "+f"(d[8]), "+f"(d[9]), "+f"(d[10]), "+f"(d[11]), "+f"(d[12]), "+f"(d[13]), "+f"(d[14]), "+f"(d[15])
               : "r"(a0), "r"(a1), "r"(a2), "r"(a3), "l"(desc), "r"(acc), "n"(TB));
}
template <int TA, int TB>
__device__ __forceinline__ void wgmma_ss32(float (&d)[16], uint64_t adesc, uint64_t desc, int acc) {
  asm volatile("{.reg .pred p; setp.ne.b32 p, %18, 0;\n"
               "wgmma.mma_async.sync.aligned.m64n32k16.f32.bf16.bf16 {%0,%1,%2,%3,%4,%5,%6,%7,%8,%9,%10,%11,%12,%13,%14,%15}, %16, %17, p, 1, 1, %19, %20;}"
               : "+f"(d[0]), "+f"(d[1]), "+f"(d[2]), "+f"(d[3]), "+f"(d[4]), "+f"(d[5]), "+f"(d[6]), "+f"(d[7]),
                 "+f"(d[8]), "+f"(d[9]), "+f"(d[10]), "+f"(d[11]), "+f"(d[12]), "+f"(d[13]), "+f"(d[14]), "+f"(d[15])
               : "l"(adesc), "l"(desc), "r"(acc), "n"(TA), "n"(TB));
}
__device__ __forceinline__ void wgmma_ss40(float (&d)[20], uint64_t adesc, uint64_t desc, int acc) {
  asm volatile("{.reg .pred p; setp.ne.b32 p, %22, 0;\n"
               "wgmma.mma_async.sync.aligned.m64n40k16.f32.bf16.bf16 {%0,%1,%2,%3,%4,%5,%6,%7,%8,%9,%10,%11,%12,%13,%14,%15,%16,%17,%18,%19}, %20, %21, p, 1, 1, 0, 1;}"
               : "+f"(d[0]), "+f"(d[1]), "+f"(d[2]), "+f"(d[3]), "+f"(d[4]), "+f"(d[5]), "+f"(d[6]), "+f"(d[7]),
                 "+f"(d[8]), "+f"(d[9]), "+f"(d[10]), "+f"(d[11]), "+f"(d[12]), "+f"(d[13]), "+f"(d[14]), "+f"(d[15]),
                 "+f"(d[16]), "+f"(d[17]), "+f"(d[18]), "+f"(d[19])
               : "l"(adesc), "l"(desc), "r"(acc));
}
__device__ __forceinline__ float rcp(float x) { float r; asm("rcp.approx.ftz.f32 %0, %1;" : "=f"(r) : "f"(x)); return r; }
__device__ __forceinline__ uint64_t make_desc(uint32_t addr, uint32_t lbo, uint32_t sbo, uint32_t swz) {
  return (uint64_t)((addr & 0x3FFFF) >> 4) | ((uint64_t)(lbo >> 4) << 16) | ((uint64_t)(sbo >> 4) << 32) | ((uint64_t)swz << 62);
}
__device__ __forceinline__ void ld_b128(const void* p, uint32_t& a, uint32_t& b, uint32_t& c, uint32_t& d) {
  asm volatile("{.reg .b128 t; .reg .b64 lo, hi; ld.relaxed.gpu.global.b128 t, [%4]; mov.b128 {lo, hi}, t; mov.b64 {%0,%1}, lo; mov.b64 {%2,%3}, hi;}"
               : "=r"(a), "=r"(b), "=r"(c), "=r"(d) : "l"(p) : "memory");
}
__device__ __forceinline__ void st_b128(void* p, uint32_t a, uint32_t b, uint32_t c, uint32_t d) {
  asm volatile("{.reg .b128 t; .reg .b64 lo, hi; mov.b64 lo, {%1,%2}; mov.b64 hi, {%3,%4}; mov.b128 t, {lo, hi}; st.relaxed.gpu.global.b128 [%0], t;}"
               ::"l"(p), "r"(a), "r"(b), "r"(c), "r"(d) : "memory");
}
__device__ __forceinline__ void ld_v4(const void* p, uint32_t& a, uint32_t& b, uint32_t& c, uint32_t& d) {
  asm volatile("ld.relaxed.gpu.global.v4.u32 {%0,%1,%2,%3}, [%4];" : "=r"(a), "=r"(b), "=r"(c), "=r"(d) : "l"(p) : "memory");
}
__device__ __forceinline__ void st_u32(void* p, uint32_t v) { asm volatile("st.relaxed.gpu.global.u32 [%0], %1;" ::"l"(p), "r"(v) : "memory"); }
__device__ __forceinline__ void sts128(uint32_t a, uint32_t x, uint32_t y, uint32_t z, uint32_t w) {
  asm volatile("st.shared.v4.u32 [%0], {%1,%2,%3,%4};" ::"r"(a), "r"(x), "r"(y), "r"(z), "r"(w) : "memory");
}
__device__ __forceinline__ void lds128f(uint32_t a, float& x, float& y, float& z, float& w) {
  asm volatile("ld.shared.v4.f32 {%0,%1,%2,%3}, [%4];" : "=f"(x), "=f"(y), "=f"(z), "=f"(w) : "r"(a) : "memory");
}
__device__ __forceinline__ void sts32f(uint32_t a, float x) { asm volatile("st.shared.f32 [%0], %1;" ::"r"(a), "f"(x) : "memory"); }
__device__ __forceinline__ void lds64f(uint32_t a, float& x, float& y) { asm volatile("ld.shared.v2.f32 {%0,%1}, [%2];" : "=f"(x), "=f"(y) : "r"(a) : "memory"); }

__device__ __forceinline__ void st_v2(void* p, uint32_t a, uint32_t b) { asm volatile("st.relaxed.gpu.global.v2.u32 [%0], {%1,%2};" ::"l"(p), "r"(a), "r"(b) : "memory"); }
__device__ __forceinline__ void ld_v2(const void* p, uint32_t& a, uint32_t& b) { asm volatile("ld.relaxed.gpu.global.v2.u32 {%0,%1}, [%2];" : "=r"(a), "=r"(b) : "l"(p) : "memory"); }
__device__ __forceinline__ uint32_t ld_u32(const void* p) { uint32_t v; asm volatile("ld.relaxed.gpu.global.u32 %0, [%1];" : "=r"(v) : "l"(p) : "memory"); return v; }
__device__ __forceinline__ uint32_t ld_acq(const unsigned* p) { uint32_t v; asm volatile("ld.acquire.gpu.global.u32 %0, [%1];" : "=r"(v) : "l"(p) : "memory"); return v; }
__device__ __forceinline__ void lds128(uint32_t a, uint32_t& x, uint32_t& y, uint32_t& z, uint32_t& w) {
  asm volatile("ld.shared.v4.u32 {%0,%1,%2,%3}, [%4];" : "=r"(x), "=r"(y), "=r"(z), "=r"(w) : "r"(a) : "memory");
}
__device__ __forceinline__ void lds64(uint32_t a, uint32_t& x, uint32_t& y) { asm volatile("ld.shared.v2.u32 {%0,%1}, [%2];" : "=r"(x), "=r"(y) : "r"(a) : "memory"); }
__device__ __forceinline__ uint32_t lds32(uint32_t a) { uint32_t v; asm volatile("ld.shared.u32 %0, [%1];" : "=r"(v) : "r"(a) : "memory"); return v; }
__device__ __forceinline__ uint32_t lds32v(uint32_t a) { uint32_t v; asm volatile("ld.volatile.shared.u32 %0, [%1];" : "=r"(v) : "r"(a) : "memory"); return v; }
__device__ __forceinline__ void sts32(uint32_t a, uint32_t v) { asm volatile("st.shared.u32 [%0], %1;" ::"r"(a), "r"(v) : "memory"); }
__device__ __forceinline__ void sts64(uint32_t a, uint32_t x, uint32_t y) { asm volatile("st.shared.v2.u32 [%0], {%1,%2};" ::"r"(a), "r"(x), "r"(y) : "memory"); }
__device__ __forceinline__ uint32_t clk() { uint64_t c; asm volatile("mov.u64 %0, %%clock64;" : "=l"(c)::"memory"); return (uint32_t)c; }
__device__ __forceinline__ uint32_t gtime() { uint64_t c; asm volatile("mov.u64 %0, %%globaltimer;" : "=l"(c)::"memory"); return (uint32_t)c; }
__device__ __forceinline__ uint32_t gtime_after(uint32_t dep) {
  uint32_t t;
  asm volatile("{.reg .pred p; .reg .u64 c; setp.ne.u32 p, %1, 0x7fc12345; mov.u64 c, 0; @p mov.u64 c, %%globaltimer; cvt.u32.u64 %0, c;}" : "=r"(t) : "r"(dep) : "memory");
  return t;
}
__device__ __forceinline__ void spin_clk_until(uint32_t t) { while ((int)(clk() - t) < 0) {} }
__device__ __forceinline__ void spin_gt_until(uint32_t t) { while ((int)(gtime() - t) < 0) {} }
template <int L> __device__ __forceinline__ uint32_t lop3(uint32_t a, uint32_t b, uint32_t c) {
  uint32_t r; asm("lop3.b32 %0, %1, %2, %3, %4;" : "=r"(r) : "r"(a), "r"(b), "r"(c), "n"(L)); return r;
}
__device__ __forceinline__ float bf_lo(uint32_t w) { return __uint_as_float(w << 16); }
__device__ __forceinline__ float bf_hi(uint32_t w) { return __uint_as_float(w & 0xffff0000u); }
#define NPR 5
__device__ __forceinline__ void probe_pages(uint32_t bar, unsigned char* p, uint32_t& ba, uint32_t& bb) {
  for (int r = 0; r < NPR; r++) {
    if (r == 1) mbar_wait(bar, 0);
    const uint32_t t0 = clk();
    uint32_t u, v, t1, t2;
    asm volatile("atom.relaxed.gpu.global.exch.b32 %0, [%1], %2;" : "=r"(u) : "l"(p), "r"(r) : "memory");
    asm volatile("atom.relaxed.gpu.global.exch.b32 %0, [%1], %2;" : "=r"(v) : "l"(p + 4096), "r"(r) : "memory");
    asm volatile("{.reg .pred p; .reg .u64 c; setp.ne.u32 p, %1, 0x7fc12345; mov.u64 c, 0; @p mov.u64 c, %%clock64; cvt.u32.u64 %0, c;}" : "=r"(t1) : "r"(u) : "memory");
    asm volatile("{.reg .pred p; .reg .u64 c; setp.ne.u32 p, %1, 0x7fc12345; mov.u64 c, 0; @p mov.u64 c, %%clock64; cvt.u32.u64 %0, c;}" : "=r"(t2) : "r"(v) : "memory");
    ba = min(ba, t1 - t0);
    bb = min(bb, t2 - t0);
  }
}
#define K_SPLIT 0
#define CH4 1
#define VDL 700
#define D1 4
#define D2 1
#define T_BAR 5
#define NOM 12
#define SPAN0 33
#define N20 19
#define TM0 8
#define MG1 16
#define MG2 88
#define ODLY 2
#define WARM 1
#define LOCP 32
#define PASS 24
#define FIXP 8
namespace rk {
constexpr uint32_t XT = 0;
constexpr uint32_t RA = 65536;
constexpr uint32_t KV = RA;
constexpr uint32_t QX = KV + 4 * 20480;
constexpr uint32_t WRES = RA + 14 * 8192;
constexpr uint32_t WOS = RA + 131072;
constexpr uint32_t OST = WOS;
constexpr uint32_t PS = WOS + 8192;
constexpr uint32_t MEMS = WOS + 16384;
constexpr uint32_t QM = MEMS + 8192;
constexpr uint32_t SC = QM + 2048;
constexpr uint32_t SR = SC + 1024;
constexpr uint32_t VM = QX;
constexpr uint32_t SF0 = PS + 4096, SF1 = VM + 8192;
constexpr uint32_t BAR = SR + 2048;
constexpr uint32_t B_QK = BAR, B_V = BAR + 120;
constexpr uint32_t B_KV = BAR + 8;
constexpr uint32_t B_XF = BAR + 40;
constexpr uint32_t B_W = BAR + 56;
constexpr uint32_t B_FREE = BAR + 88;
constexpr uint32_t B_OF = BAR + 96, B_PUB = BAR + 112;
constexpr uint32_t B_MEM = BAR + 128;
constexpr uint32_t B_Q = BAR + 160;
constexpr uint32_t B_OK = BAR + 192, B_FIX = BAR + 200;
constexpr uint32_t TK = BAR + 256;
constexpr uint32_t TK_X = TK + 48, TK_Q = TK + 56, TK_PG = TK + 64;
constexpr uint32_t TABS = BAR + 384;
constexpr uint32_t TM = BAR + 1024;
constexpr uint32_t SMEM = TM + 4096 + 1024;
constexpr int NB_P = 1, NB_T = 2, NB_X = 3, NB_S = 4, NB_TD = 5, NB_TAB = 6, NB_M = 7;
constexpr float kExpScale = 0.08838834764831845f * 1.4426950408889634f;
constexpr int kSplit = K_SPLIT;
}

__device__ __forceinline__ void r_proj_issue(const uint32_t (&w)[112], float (&d)[16], uint32_t sb, int seg, int warp, int j0, int j1) {
  using namespace rk;
  const uint64_t desc = make_desc(sb + XT + (seg & 1) * 32768, 16, 1024, 1);
  const uint64_t adesc = make_desc(sb + WRES + (warp >> 2) * 8192, 1024, 1024, 1);
  wg_fence();
#pragma unroll
  for (int i = 0; i < 32; i++) {
    if (i < j0 || i >= j1) continue;
    const int j = i < 8 ? i : (i - 8) % 6 == 0 ? 28 + (i - 8) / 6 : i - 1 - (i - 8) / 6;
    const uint64_t bd = desc + (uint64_t)(((j >> 2) * 4096 + (j & 3) * 32) >> 4);
    if (j < 28) wgmma_rs32<0>(d, w[4 * j], w[4 * j + 1], w[4 * j + 2], w[4 * j + 3], bd, j > 0);
    else wgmma_ss32<1, 0>(d, adesc + (uint64_t)((j - 28) * 128), bd, 1);
  }
  wg_commit();
}
__device__ __forceinline__ void r_store_rows(const float (&d)[16], uint32_t dst, int w4, uint32_t lane) {
  const uint32_t a = dst + ((lane >> 4) * 8 + (lane & 7)) * 128 + (((2 * w4 + ((lane >> 3) & 1)) ^ (lane & 7)) << 4);
  stsm4t(a, pack2(d[0], d[1]), pack2(d[2], d[3]), pack2(d[4], d[5]), pack2(d[6], d[7]));
  stsm4t(a + 2048, pack2(d[8], d[9]), pack2(d[10], d[11]), pack2(d[12], d[13]), pack2(d[14], d[15]));
}
template <bool R0>
__device__ __forceinline__ void r_proj_store(const float (&d)[16], uint32_t sb, int seg, int warp, uint32_t lane, uint32_t rank) {
  using namespace rk;
  if (R0) {
    r_store_rows(d, sb + QX + (seg & 3) * 8192 + (warp >> 2) * 4096, warp & 3, lane);
  } else {
    const uint32_t a = sb + KV + (seg & 3) * 20480 + (rank - 1) * 10240 + (lane >> 4) * 2048 + (16 * warp + (lane & 15)) * 16;
    stsm4(a, pack2(d[0], d[1]), pack2(d[2], d[3]), pack2(d[4], d[5]), pack2(d[6], d[7]));
    stsm4(a + 4096, pack2(d[8], d[9]), pack2(d[10], d[11]), pack2(d[12], d[13]), pack2(d[14], d[15]));
  }
  if (R0) fence_async_smem();
}
__device__ __forceinline__ void r_proj_share(uint32_t sb, int seg, uint32_t rank) {
  using namespace rk;
  const uint32_t bar = sb + B_KV + 8 * (seg & 3), src = sb + KV + (seg & 3) * 20480 + (rank - 1) * 10240;
  if (rank != 0) {
    fence_async_smem();
    bulk_s2c(mapa(src, 3 - rank), src, 8192, mapa(bar, 3 - rank));
    bulk_s2c(mapa(src, 0), src, 8192, mapa(bar, 0));
  }
  mbar_arrive_tx(bar, rank == 0 ? 16384 : 8192);
}
__device__ __forceinline__ void r_flag_o(int seg, uint32_t head) {
  const uint32_t idx = seg < kS0 ? C_O + (seg >> 2) : C_S + (seg - kS0) * 8 + (head >> 2);
  asm volatile("cp.async.bulk.wait_group 0; red.relaxed.gpu.global.add.u32 [%0], 1;" ::"l"(&g_cnt[idx]) : "memory");
}

template <int I>
__device__ __forceinline__ void r_vo_issue(const uint32_t (&wo)[64], float (&d)[16], uint32_t sb, int seg) {
  using namespace rk;
  const uint64_t desc = make_desc(sb + KV + (seg & 3) * 20480 + 10240, 128, 2048, 0);
  const uint64_t adesc = make_desc(sb + WOS, 16, 1024, 1);
  wg_fence();
#pragma unroll
  for (int kk = 0; kk < 8; kk++) {
    if (I < 2) wgmma_rs32<1>(d, wo[32 * I + 4 * kk], wo[32 * I + 4 * kk + 1], wo[32 * I + 4 * kk + 2], wo[32 * I + 4 * kk + 3], desc + (uint64_t)(kk * 16), kk > 0);
    else wgmma_ss32<0, 1>(d, adesc + (uint64_t)(((kk >> 2) * 8192 + (kk & 3) * 32) >> 4), desc + (uint64_t)(kk * 16), kk > 0);
  }
  wg_commit();
}
__device__ __forceinline__ void r_vo_issue2(const uint32_t (&wo)[64], float (&d0)[16], float (&d2)[16], uint32_t sb, int seg) {
  using namespace rk;
  const uint64_t desc = make_desc(sb + KV + (seg & 3) * 20480 + 10240, 128, 2048, 0);
  const uint64_t adesc = make_desc(sb + WOS, 16, 1024, 1);
  wg_fence();
#pragma unroll
  for (int kk = 0; kk < 8; kk++) {
    wgmma_rs32<1>(d0, wo[4 * kk], wo[4 * kk + 1], wo[4 * kk + 2], wo[4 * kk + 3], desc + (uint64_t)(kk * 16), kk > 0);
    wgmma_ss32<0, 1>(d2, adesc + (uint64_t)(((kk >> 2) * 8192 + (kk & 3) * 32) >> 4), desc + (uint64_t)(kk * 16), kk > 0);
  }
  wg_commit();
}
__device__ __forceinline__ void pack16(uint32_t* o, const float (&d)[16]) {
#pragma unroll
  for (int j = 0; j < 8; j++) o[j] = pack2(d[2 * j], d[2 * j + 1]);
}

template <int NT>
__device__ __forceinline__ void r_attn_role(uint32_t sb, int tw, int lane, uint32_t rank, uint32_t head, const bf16* __restrict__ Wo) {
  using namespace rk;
  const int g = lane >> 2, t = lane & 3;
  const int tile0 = (NT == 2 ? 0 : 12 * (int)rank - 4) + tw;
  uint32_t wo[64];
  const uint32_t woa = sb + WOS + (16 * tw + (lane & 15)) * 128;
  const uint32_t wx = (lane >> 4) ^ (lane & 7);
  {
    uint32_t wt[32 * NT];
#pragma unroll
    for (int i = 0; i < NT; i++) {
      const uint32_t* src = reinterpret_cast<const uint32_t*>(Wo + (size_t)(head * 128 + 2 * t) * kD + (tile0 + 4 * i) * 16 + 2 * g);
#pragma unroll
      for (int kk = 0; kk < 8; kk++) {
        wt[32 * i + 4 * kk] = __ldg(src + (16 * kk) * (kD / 2));
        wt[32 * i + 4 * kk + 1] = __ldg(src + (16 * kk + 1) * (kD / 2));
        wt[32 * i + 4 * kk + 2] = __ldg(src + (16 * kk + 8) * (kD / 2));
        wt[32 * i + 4 * kk + 3] = __ldg(src + (16 * kk + 9) * (kD / 2));
      }
    }
#pragma unroll
    for (int j = 0; j < 16 * NT; j++) {
      const uint32_t x = wt[2 * j], y = wt[2 * j + 1];
      wt[2 * j] = __byte_perm(x, y, 0x5410);
      wt[2 * j + 1] = __byte_perm(x, y, 0x7632);
    }
#pragma unroll
    for (int j = 0; j < 64; j++) wo[j] = wt[j];
    if (NT == 3) {
#pragma unroll
      for (int kk = 0; kk < 8; kk++)
        stsm4(woa + (kk >> 2) * 8192 + (((2 * (kk & 3)) ^ wx) << 4), wt[32 * NT - 32 + 4 * kk], wt[32 * NT - 31 + 4 * kk], wt[32 * NT - 30 + 4 * kk], wt[32 * NT - 29 + 4 * kk]);
    } else if (tw == 0) {
      sts128(sb + PS + 5 * 512 + lane * 16, 0u, 0u, 0u, 0u);
    }
    fence_async_smem();
    bar_sync(NB_T, 128);
  }
  uint64_t mail[NT];
  TSTAMP(tw == 0 && lane == 0, blockIdx.x * 80 + 78);
  cluster_wait();
  uint32_t vox[8 * NT];
  uint32_t la = sb + lane * 16;
  OPAQUE(la);
  const uint32_t vma = la + VM + tw * 512;
  mbar_wait(sb + B_KV, 0);
  {
    float d[16];
    r_vo_issue<0>(wo, d, sb, 0); wg_wait<0>(); pack16(vox, d);
    r_vo_issue<1>(wo, d, sb, 0); wg_wait<0>(); pack16(vox + 8, d);
    if (NT == 3) { r_vo_issue<2>(wo, d, sb, 0); wg_wait<0>(); pack16(vox + 8 * NT - 8, d); }
  }
  bar_sync(NB_TAB, NT == 2 ? 512 : 256);
#pragma unroll
  for (int i = 0; i < NT; i++) {
    const uint32_t unit = (tile0 + 4 * i) * 4 + (g >> 2) * 2 + (t >> 1);
    mail[i] = (uint64_t)(g_mail + (unit * 8192 + (lds32(sb + TABS + unit * 4) & 4096u) + head * 64 + (t & 1) * 32 + (g & 3) * 8));
  }
  if (NT == 3) {
    sts128(vma, (uint32_t)mail[0], (uint32_t)(mail[0] >> 32), (uint32_t)mail[1], (uint32_t)(mail[1] >> 32));
    sts64(vma + 2048, (uint32_t)mail[NT - 1], (uint32_t)(mail[NT - 1] >> 32));
  }
  for (int s = 0;; s++) {
    {
      uint32_t redo = 0;
      bool pend = true;
      mbar_wait(sb + B_V, s & 1);
      while (true) {
        constexpr uint32_t kOnes = 0x3F803F80u;
        const uint32_t va = la + (la & 256) * 3 + KV + (s & 3) * 20480 + 10240 + 8192;
        float vm[4][4];
        uint32_t b[16], dep = 0;
#pragma unroll
        for (int kk = 0; kk < 4; kk++) ldsm4t(va + kk * 256, b[4 * kk], b[4 * kk + 1], b[4 * kk + 2], b[4 * kk + 3]);
        TMARKD(tw == 0, 3, b[0]);
#pragma unroll
        for (int kk = 0; kk < 4; kk++) {
          if (kk == T_BAR) dep = __float_as_uint(vm[3][0]);
#pragma unroll
          for (int c = 0; c < 4; c++) {
            const uint32_t* p = &wo[16 * c + 4 * kk];
            const uint32_t* q = &b[4 * kk + 2 * (c & 1)];
            if (kk == 0) mma16z(vm[c], p[0], p[1], p[2], p[3], q[0], q[1]);
            else mma16(vm[c], p[0], p[1], p[2], p[3], q[0], q[1]);
          }
        }
        if (T_BAR == 4) dep = __float_as_uint(vm[3][0]);
        uint32_t vp[4];
#pragma unroll
        for (int i = 0; i < 2; i++) {
          vp[2 * i] = pack2(vm[2 * i][0] + vm[2 * i + 1][0], vm[2 * i][1] + vm[2 * i + 1][1]);
          vp[2 * i + 1] = pack2(vm[2 * i][2] + vm[2 * i + 1][2], vm[2 * i][3] + vm[2 * i + 1][3]);
        }
        if (T_BAR == 5) dep = vp[0] | vp[1] | vp[2] | vp[3];
        bar_sync_after(NB_S, NT == 3 ? 480 : 224, dep, redo);
        uint32_t p[6], v3[4];
        ldsm4t(la + redo + SC, p[0], p[1], p[2], p[3]);
        ldsm2t(((la + redo) & ~0x180u) + SC + 512, p[4], p[5]);
        if (NT == 3) lds128(vma + 4096, v3[0], v3[1], v3[2], v3[3]);
        TMARKD(tw == 0, 4, p[0]);
        float o[NT][4], sa[4], sc[4];
        mma16z(sa, kOnes, kOnes, kOnes, kOnes, p[0], p[1]);
        mma16z(sc, kOnes, kOnes, kOnes, kOnes, p[2], p[3]);
#pragma unroll
        for (int i = 0; i < 2; i++) mma8z(o[i], vp[2 * i], vp[2 * i + 1], p[4]);
        if (NT == 3) mma16z(o[NT - 1], v3[0], v3[1], v3[2], v3[3], p[4], p[5]);
        mma8(sa, kOnes, kOnes, p[4]);
#pragma unroll
        for (int i = 0; i < NT; i++) mma16(o[i], vox[8 * i], vox[8 * i + 1], vox[8 * i + 2], vox[8 * i + 3], p[0], p[1]);
        if (NT == 3) {
          asm volatile("ld.shared.v2.u64 {%0,%1}, [%2];" : "=l"(mail[0]), "=l"(mail[1]) : "r"(vma) : "memory");
          asm volatile("ld.shared.u64 %0, [%1];" : "=l"(mail[NT - 1]) : "r"(vma + 2048) : "memory");
        }
#pragma unroll
        for (int i = 0; i < NT; i++) mma16(o[i], vox[8 * i + 4], vox[8 * i + 5], vox[8 * i + 6], vox[8 * i + 7], p[2], p[3]);
        const float s0 = sa[0] + sc[0], s1 = sa[1] + sc[1];
        const float i0 = rcp(s0), i1 = rcp(s1);
        const bool ok = redo ? pend : max(__float_as_uint(s0) - 0x30000000u, __float_as_uint(s1) - 0x30000000u) < 0x1F000000u;
        const uint32_t tag = (s + 1) & 1;
#pragma unroll
        for (int i = 0; i < NT; i++)
          asm volatile("{.reg .pred q; setp.ne.u32 q, %3, 0; @q st.relaxed.gpu.global.v2.u32 [%0], {%1,%2};}" ::"l"(mail[i]),
                       "r"(lop3<0xea>(pack2(o[i][0] * i0, o[i][2] * i0), ~1u, tag)), "r"(pack2(o[i][1] * i1, o[i][3] * i1)), "r"((uint32_t)ok) : "memory");
        if (redo) break;
        if (NT == 3) bar_arrive(NB_TD, 384);
        sts32(sb + TK + tw * 4, gtime_after(ok));
        if (NT == 3 && lane == 0) mbar_arrive(sb + B_PUB);
        TMARKD(tw == 0, 5, ok);
        if (__all_sync(~0u, ok)) break;
        float sv[10];
        const uint32_t ra = sb + SR + t * 128 + (g >> 1) * 16 + (g & 1) * 4;
#pragma unroll
        for (int j = 0; j < 8; j++) sv[j] = __uint_as_float(lds32(ra + (j >> 2) * 512 + ((j >> 1) & 1) * 8 + (j & 1) * 64));
#pragma unroll
        for (int j = 0; j < 2; j++) sv[8 + j] = __uint_as_float(lds32(ra + 1024 + j * 64));
        float m = sv[0];
#pragma unroll
        for (int j = 1; j < 10; j++) m = fmaxf(m, sv[j]);
        m = fmaxf(m, __shfl_xor_sync(~0u, m, 1));
        const float mb = -fmaxf(m, __shfl_xor_sync(~0u, m, 2)) * kExpScale;
#pragma unroll
        for (int j = 0; j < 5; j++) p[j] = pack2(ex2(fmaf(sv[2 * j], kExpScale, mb)), ex2(fmaf(sv[2 * j + 1], kExpScale, mb)));
        redo = (NT == 2 ? SF0 : SF1) - SC + tw * 1024;
        pend = !ok;
        stsm4t(la + redo + SC, p[0], p[1], p[2], p[3]);
        stsm1t(la + redo + SC + 512, p[4]);
        __syncwarp();
      }
      if (tw == 0 && lane == 0) {
        mbar_arrive_tx(sb + B_QK, rank == 2 ? 4096 : 2048);
        mbar_arrive_tx(sb + B_V, rank == 2 ? 0 : 2048);
      }
    }
    if (NT == 3) {
      if (s + 1 == kNSeg) break;
      mbar_wait(sb + B_KV + 8 * ((s + 1) & 3), ((s + 1) >> 2) & 1);
      float d0[16], d1[16];
      if (VDL) spin_clk_until(clk() + VDL);
      r_vo_issue2(wo, d0, d1, sb, s + 1);
      wg_wait<0>();
      pack16(vox, d0);
      r_vo_issue<1>(wo, d0, sb, s + 1);
      pack16(vox + 8 * NT - 8, d1);
      wg_wait<0>();
      pack16(vox + 8, d0);
    } else {
      float sc[20], d0[16], d1[16];
      mbar_wait(sb + B_Q + 8 * (s & 3), (s >> 2) & 1);
      {
        const uint64_t qd = make_desc(sb + QX + (s & 3) * 8192, 16, 1024, 1), kd = make_desc(sb + KV + (s & 3) * 20480, 128, 2048, 0);
        wg_fence();
#pragma unroll
        for (int kk = 0; kk < 8; kk++) wgmma_ss40(sc, qd + (uint64_t)(((kk >> 2) * 4096 + (kk & 3) * 32) >> 4), kd + (uint64_t)(kk * 16), kk > 0);
        wg_commit();
        wg_wait<0>();
      }
      if (tw < 2) {
        const int dl = 16 * tw + g - 2 * t;
        float m0 = fmaxf(sc[16], sc[17]), m1 = fmaxf(sc[18], sc[19]);
#pragma unroll
        for (int n = 0; n < 4; n++) {
          if (8 * n > dl) sc[4 * n] = -INFINITY;
          if (8 * n + 1 > dl) sc[4 * n + 1] = -INFINITY;
          if (8 * n - 8 > dl) sc[4 * n + 2] = -INFINITY;
          if (8 * n - 7 > dl) sc[4 * n + 3] = -INFINITY;
          m0 = fmaxf(m0, fmaxf(sc[4 * n], sc[4 * n + 1]));
          m1 = fmaxf(m1, fmaxf(sc[4 * n + 2], sc[4 * n + 3]));
        }
        m0 = fmaxf(m0, __shfl_xor_sync(~0u, m0, 1)); m1 = fmaxf(m1, __shfl_xor_sync(~0u, m1, 1));
        m0 = fmaxf(m0, __shfl_xor_sync(~0u, m0, 2)); m1 = fmaxf(m1, __shfl_xor_sync(~0u, m1, 2));
        m0 *= -kExpScale; m1 *= -kExpScale;
        float s0 = 0.f, s1 = 0.f;
#pragma unroll
        for (int n = 0; n < 5; n++) {
          sc[4 * n] = ex2(fmaf(sc[4 * n], kExpScale, m0)); sc[4 * n + 1] = ex2(fmaf(sc[4 * n + 1], kExpScale, m0));
          sc[4 * n + 2] = ex2(fmaf(sc[4 * n + 2], kExpScale, m1)); sc[4 * n + 3] = ex2(fmaf(sc[4 * n + 3], kExpScale, m1));
          s0 += sc[4 * n] + sc[4 * n + 1]; s1 += sc[4 * n + 2] + sc[4 * n + 3];
        }
        s0 += __shfl_xor_sync(~0u, s0, 1); s1 += __shfl_xor_sync(~0u, s1, 1);
        s0 += __shfl_xor_sync(~0u, s0, 2); s1 += __shfl_xor_sync(~0u, s1, 2);
        const float i0 = rcp(s0), i1 = rcp(s1);
        uint32_t p[10];
#pragma unroll
        for (int n = 0; n < 5; n++) { p[2 * n] = pack2(sc[4 * n] * i0, sc[4 * n + 1] * i0); p[2 * n + 1] = pack2(sc[4 * n + 2] * i1, sc[4 * n + 3] * i1); }
        const uint32_t pa = sb + PS + (lane >> 4) * 512 + (16 * tw + (lane & 15)) * 16;
        stsm4(pa, p[0], p[1], p[2], p[3]);
        stsm4(pa + 1024, p[4], p[5], p[6], p[7]);
        stsm2(pa + 2048, p[8], p[9]);
        fence_async_smem();
      }
      TMARKD(tw == 0, 10, 0);
      bar_sync(NB_T, 128);
      if (s + 1 < kNSeg) {
        mbar_wait(sb + B_KV + 8 * ((s + 1) & 3), ((s + 1) >> 2) & 1);
        mbar_wait(sb + B_PUB, s & 1);
      }
      {
        const uint32_t vb = sb + KV + (s & 3) * 20480 + 10240;
        const uint64_t pd = make_desc(sb + PS, 512, 128, 0);
        const uint64_t vd = make_desc(vb, 2048, 128, 0), vd2 = make_desc(vb + 8192, 0, 128, 0);
        wg_fence();
        wgmma_ss32<0, 0>(d0, vd, pd, 0);
        wgmma_ss32<0, 0>(d1, vd + 64, pd, 0);
        wgmma_ss32<0, 0>(d0, vd + 256, pd + 64, 1);
        wgmma_ss32<0, 0>(d1, vd + 256 + 64, pd + 64, 1);
        wgmma_ss32<0, 0>(d0, vd2, pd + 128, 1);
        wgmma_ss32<0, 0>(d1, vd2 + 64, pd + 128, 1);
        wg_commit();
      }
      wg_wait<0>();
      r_store_rows(d0, sb + OST, tw, lane);
      r_store_rows(d1, sb + OST + 4096, tw, lane);
      r_vo_issue<0>(wo, d0, sb, s + 1);
      fence_async_smem();
      __syncwarp();
      if (lane == 0) mbar_arrive(sb + B_OF);
      r_vo_issue<1>(wo, d1, sb, s + 1);
      wg_wait<0>();
      if (s + 1 == kNSeg) break;
      pack16(vox, d0);
      pack16(vox + 8, d1);
    }
    TMARKD(tw == 0, 6, vox[8 * NT - 1]);
  }
}

__device__ __forceinline__ void r_score_role(uint32_t sb, int mw, int lane, uint32_t nbar) {
  using namespace rk;
  for (int s = 0; s < kNSeg; s++) {
    uint32_t ln = lane;
    OPAQUE(ln);
    const uint32_t ka = sb + KV + (s & 3) * 20480 + (2 * mw + ((ln >> 3) & 1)) * 2048 + ((ln >> 4) * 8 + (ln & 7)) * 16;
    const uint32_t qa = sb + QM + ln * 16;
    uint32_t kf[32], q[16];
    mbar_wait(sb + B_KV + 8 * (s & 3), (s >> 2) & 1);
#pragma unroll
    for (int j = 0; j < 8; j++) ldsm4t(ka + j * 256, kf[4 * j], kf[4 * j + 1], kf[4 * j + 2], kf[4 * j + 3]);
    mbar_wait(sb + B_QK, s & 1);
#pragma unroll
    for (int i = 0; i < 4; i++) ldsm4t(qa + i * 512, q[4 * i], q[4 * i + 1], q[4 * i + 2], q[4 * i + 3]);
    float c[4][4];
#pragma unroll
    for (int j = 0; j < 4; j++) mma16z(c[j], kf[4 * j], kf[4 * j + 1], kf[4 * j + 2], kf[4 * j + 3], q[2 * j], q[2 * j + 1]);
#pragma unroll
    for (int j = 4; j < 8; j++) mma16(c[j - 4], kf[4 * j], kf[4 * j + 1], kf[4 * j + 2], kf[4 * j + 3], q[2 * j], q[2 * j + 1]);
    float v[4];
#pragma unroll
    for (int i = 0; i < 4; i++) v[i] = (c[0][i] + c[1][i]) + (c[2][i] + c[3][i]);
    sts128(qa + (SR - QM) + mw * 512, __float_as_uint(v[0]), __float_as_uint(v[1]), __float_as_uint(v[2]), __float_as_uint(v[3]));
    stsm2(qa + (SC - QM) + mw * 256, pack2(ex2(v[0] * kExpScale), ex2(v[1] * kExpScale)), pack2(ex2(v[2] * kExpScale), ex2(v[3] * kExpScale)));
    bar_arrive(NB_S, nbar);
    TMARKD(mw == 0, 13, 0);
  }
}

__device__ __forceinline__ void r_mscore_role(uint32_t sb, int lane, uint32_t rank, uint32_t head, const CUtensorMap* tmX) {
  using namespace rk;
  const uint32_t qa = sb + QM + lane * 16;
  const uint32_t ep = ld_u32(&g_cnt[C_O + 7]) / 128 + 1;
  uint32_t local = 7;
  for (int s = 0; s < kNSeg; s++) {
    const uint32_t ka = sb + KV + (s & 3) * 20480 + 8192 + (((lane >> 3) & 1) * 2 + (lane >> 4)) * 128 + (lane & 7) * 16;
    uint32_t km[16], q[16];
    mbar_wait(sb + B_QK, s & 1);
#pragma unroll
    for (int i = 0; i < 4; i++) {
      ldsm4t(ka + i * 512, km[4 * i], km[4 * i + 1], km[4 * i + 2], km[4 * i + 3]);
      ldsm4t(qa + i * 512, q[4 * i], q[4 * i + 1], q[4 * i + 2], q[4 * i + 3]);
    }
    float c[4][4];
#pragma unroll
    for (int j = 0; j < 4; j++) mma16z(c[j], km[4 * (j >> 1)], km[4 * (j >> 1) + 1], km[4 * (j >> 1) + 2], km[4 * (j >> 1) + 3], q[2 * j], q[2 * j + 1]);
#pragma unroll
    for (int j = 4; j < 8; j++) mma16(c[j - 4], km[4 * (j >> 1)], km[4 * (j >> 1) + 1], km[4 * (j >> 1) + 2], km[4 * (j >> 1) + 3], q[2 * j], q[2 * j + 1]);
    const float v0 = (c[0][0] + c[1][2]) + (c[2][0] + c[3][2]), v1 = (c[0][1] + c[1][3]) + (c[2][1] + c[3][3]);
    sts64(qa + (SR - QM) + 1024, __float_as_uint(v0), __float_as_uint(v1));
    sts32(sb + SC + 512 + lane * 4, pack2(ex2(v0 * kExpScale), ex2(v1 * kExpScale)));
    bar_arrive(NB_S, rank == 0 ? 224 : 480);
    TMARKD(1, 19, 0);
    if (lane == 0) {
      mbar_wait(sb + B_V, s & 1);
      const int sn = s + (rank == 0 ? 3 : 4);
      const uint32_t xf = sb + B_XF + 8 * (sn & 1);
      bool ready = false;
      if (rank == 0) {
        local >>= 1;
        if (local & 1) mbar_arrive(sb + B_Q + 8 * ((s + 1) & 3));
        if (s) r_flag_o(s - 1, head);
        if (sn < kNSeg) {
          ready = (int)(ld_acq(&g_cnt[C_Q + (sn >> 2) * 16 + (head >> 1)]) - 2 * ep) >= 0;
          sts32(sb + TK_Q + (sn & 1) * 4, ready);
          if (ready) {
            const bf16* src = g_q + (size_t)((sn >> 2) * 64 + head * 2) * 8192 + (sn & 3) * 2048;
            const uint32_t bq = sb + B_Q + 8 * (sn & 3), dst = sb + QX + (sn & 3) * 8192;
            asm volatile("fence.proxy.async.global;" ::: "memory");
            mbar_arrive_tx(bq, 8192);
            bulk_g2s(dst, src, 4096, bq);
            bulk_g2s(dst + 4096, src + 8192, 4096, bq);
            mbar_arrive(xf);
          } else {
            local |= 4;
          }
        }
      }
      if (sn < kNSeg && !ready) {
        mbar_arrive_tx(xf, 32768);
        tma_3d(sb + XT + (sn & 1) * 32768, tmX, 0, sn * 32, 0, xf);
      }
      if (rank) mbar_wait(sb + B_PUB, s & 1);
      if (s + 2 < kNSeg) r_proj_share(sb, s + 2, rank);
      if (rank == 0) {
        mbar_wait(sb + B_OF, s & 1);
        spin_gt_until(lds32(sb + TK_X + 4));
        bf16* dst = g_o + (size_t)((s >> 2) * 64 + head * 2) * 8192 + (s & 3) * 2048;
        bulk_s2g(dst, sb + OST, 4096);
        bulk_s2g(dst + 8192, sb + OST + 4096, 4096);
        asm volatile("cp.async.bulk.commit_group; cp.async.bulk.wait_group.read 0;" ::: "memory");
      }
    }
    if (s == 5 && rank == 0 && lane < 2) st_u32(&g_tab[lane * 32 + head], 0u);
    __syncwarp();
  }
  if (rank == 0 && lane == 0) {
    r_flag_o(kNSeg - 1, head);
    TSTAMP(1, blockIdx.x * 80 + 3);
  }
}

__device__ __forceinline__ void r_timer_role(uint32_t sb, int lane, bool red) {
  using namespace rk;
  int span = SPAN0 * 16, n2 = N20 * 16;
  unsigned char* anc = g_pub + 3584;
  if (lane == 0) mbar_arrive(sb + B_OK);
  uint32_t stat = 0, fix = 0, x2 = 0;
  bool calm = false;
  mbar_wait(sb + B_QK, 0);
  mbar_wait(sb + B_V, 0);
  uint32_t tm = (gtime() >> 5) - TM0;
  for (int s = 0;; s++) {
    TSTAMP(lane == 0, blockIdx.x * 80 + 8 + s);
    if (s + 1 == kNSeg) break;
    const uint32_t tg = (uint32_t)(s + 1) << 24;
    if (lane < 2) st_u32(anc + (s & 1) * 8192 + lane * 4096 + blockIdx.x * 4, tg | stat | (tm & 4095u));
    uint32_t an[4], pg[4];
    const unsigned char* anr = anc + (s & 1) * 8192 + lds32(sb + TK_PG + (s & 1) * 4) + min(lane, 23) * 16;
    lds128(sb + TK_PG + (s & 1) * 16, pg[0], pg[1], pg[2], pg[3]);
    mbar_wait(sb + B_QK, s & 1);
    mbar_wait(sb + B_V, s & 1);
    int budget = 1 << 18;
    do {
      spend(budget);
      ld_v4(anr, an[0], an[1], an[2], an[3]);
    } while (__any_sync(~0u, max(max(an[0] - tg, an[1] - tg), max(an[2] - tg, an[3] - tg)) >= (1u << 24)));
    TMARKV(1, 29, (1 << 18) - 1 - budget);
    int dm = -2048;
#pragma unroll
    for (int i = 0; i < 4; i++) dm = max(dm, (int)((an[i] - tm) << 20) >> 20);
    tm += __reduce_max_sync(~0u, dm);
    const int sp = span >> 4;
    const uint32_t x1 = tm + sp;
    sts32(sb + TK_X, x1 << 5);
    if (red) bar_arrive(NB_M, 288);
    TMARKD(1, 17, x1);
    const int need = (__reduce_max_sync(~0u, max(max(an[0], an[1]), max(an[2], an[3]))) >> 18) & 63;
    const int mpub = __reduce_max_sync(~0u, max(max(an[0] & 0x3f000u, an[1] & 0x3f000u), max(an[2] & 0x3f000u, an[3] & 0x3f000u))) >> 12;
    TMARKV(1, 26, need); TMARKV(1, 27, mpub);
    if (s > WARM) {
      const int sh = s < 8 ? 1 : 3;
      if (calm) span += (min(need, sp + 3) * 16 + MG1 - span) >> sh;
      n2 += (min(mpub, (n2 >> 4) + 2) * 16 + MG2 - n2) >> sh;
    }
    calm = (int)(tm - x2) <= NOM + 1;
    x2 = x1 + (n2 >> 4);
    sts32(sb + TK_X + 4, (x2 + ODLY) << 5);
    TMARKV(1, 20, x1 << 5); TMARKV(1, 21, x2 << 5);
    const unsigned char* pp = g_pub + (s & 1) * 32768;
    const uint32_t late = x2 + (red && !lds32(sb + TK_Q + (s & 1) * 4) ? LOCP : NOM);
    uint32_t t2 = x2 << 5, bar = sb + B_MEM, par = (s + 1) & 1, tf = 0;
    OPAQUE(t2);
    if (lane < 4) mbar_arrive_tx(bar + 8 * lane, lane < 2 ? 1024 : 1024 << (lane - 1));
    mbar_wait(sb + B_PUB, s & 1);
    for (budget = 1 << 18;;) {
      spin_gt_until(t2);
      asm volatile("{.reg .pred p; elect.sync _|p, 0xffffffff;\n"
                   "@p cp.async.bulk.shared::cluster.global.mbarrier::complete_tx::bytes [%0 + 7168], [%2 + 1024], 1024, [%1];\n"
                   "@p cp.async.bulk.shared::cluster.global.mbarrier::complete_tx::bytes [%0 + 6144], [%2], 1024, [%1 + 8];\n"
                   "@p cp.async.bulk.shared::cluster.global.mbarrier::complete_tx::bytes [%0], [%3], 2048, [%1 + 16];\n"
                   "@p cp.async.bulk.shared::cluster.global.mbarrier::complete_tx::bytes [%0 + 2048], [%4], 2048, [%1 + 24];\n"
                   "@p cp.async.bulk.shared::cluster.global.mbarrier::complete_tx::bytes [%0 + 4096], [%5], 2048, [%1 + 24];}"
                   ::"r"(sb + MEMS), "r"(bar), "l"(pp + (3 * 8192 + pg[3])), "l"(pp + pg[0]), "l"(pp + (8192 + pg[1])), "l"(pp + (2 * 8192 + pg[2])) : "memory");
      TMARKD(!tf, 8, 0);
      const int e = (int)(lds32(sb + TK + min(lane, red ? 11 : 3) * 4) - (x1 << 5)) >> 5;
      const int post = __reduce_max_sync(~0u, lane < 4 ? e : -64) + sp + D1, pub = __reduce_max_sync(~0u, e) + D2;
      stat = min(max(post, 0), 63) << 18 | min(max(pub, 0), 63) << 12;
#pragma unroll
      for (int i = 3; i >= 0; i--) mbar_wait(bar + 8 * i, par);
      tm = gtime();
      TMARKD(1, 11, 0);
      uint32_t m = 0;
#pragma unroll
      for (int i = 0; i < 8; i++) m = max(m, lds32v(sb + MEMS + i * 1024 + lane * 32 + (lane >> 2) * 4));
      const bool bad = __any_sync(~0u, m == ~0u);
      if (bad && lane < 4) mbar_arrive_tx(sb + B_FIX + 8 * lane, lane < 2 ? 1024 : 1024 << (lane - 1));
      if (!bad) break;
      spend(budget);
      tf = tf ? tf : tm | 1u;
      bar = sb + B_FIX; par = fix; fix ^= 1;
      TMARKV(1, 30, (1 << 18) - budget);
    }
    tm = (tf ? tf + max((int)(tm - tf) + 32 * FIXP, 32 * PASS) : tm) >> 5;
    if (lane == 0) mbar_arrive(sb + B_OK);
    if ((int)((late - tm) << 5) > 0) tm = late;
  }
}

template <bool R0>
__device__ __forceinline__ void r_proj_role(uint32_t sb, int warp, int lane, uint32_t rank, uint32_t head, const CUtensorMap* tmX) {
  using namespace rk;
  uint32_t w[112];
  {
    const uint32_t wa = sb + RA + (warp >> 2) * 8192 + ((lane >> 4) * 8 + (lane & 7)) * 128 + (((2 * (warp & 3) + ((lane >> 3) & 1)) ^ (lane & 7)) << 4);
#pragma unroll
    for (int c = 0; c < 4; c++) {
      mbar_wait(sb + B_W + 8 * c, 0);
#pragma unroll
      for (int jj = 0; jj < 8; jj++) {
        const int j = 8 * c + jj;
        if (j < 28) ldsm4t(wa + (j >> 2) * 16384 + (j & 3) * 2048, w[4 * j], w[4 * j + 1], w[4 * j + 2], w[4 * j + 3]);
      }
    }
  }
  __syncwarp();
  TSTAMP(threadIdx.x == 0, blockIdx.x * 80 + 1);
  if (lane + (w[111] & blockIdx.y) < 3) asm volatile("mbarrier.arrive.relaxed.cluster.shared::cluster.b64 _, [%0];" ::"r"(mapa(sb + B_FREE, lane)) : "memory");
  mbar_wait_cl(sb + B_FREE, 0);
  TSTAMP(threadIdx.x == 0, blockIdx.x * 80 + 79);
  constexpr int LA = R0 ? 2 : 3;
  for (int sg = 0; sg < LA; sg++) {
    float d[16];
    mbar_wait(sb + B_XF + 8 * (sg & 1), sg >> 1);
    r_proj_issue(w, d, sb, sg, warp, 0, 32);
    wg_wait<0>();
    r_proj_store<R0>(d, sb, sg, warp, lane, rank);
    bar_sync(NB_P, 256);
    TSTAMP(threadIdx.x == 0 && sg < 2, blockIdx.x * 80 + 6 + sg);
    if (threadIdx.x == 0 && sg < 2) {
      r_proj_share(sb, sg, rank);
      if (R0 && sg == 0) mbar_arrive(sb + B_Q);
      if (sg < LA - 1) {
        mbar_arrive_tx(sb + B_XF + 8 * sg, 32768);
        tma_3d(sb + XT + sg * 32768, tmX, 0, 64 + 32 * sg, 0, sb + B_XF + 8 * sg);
      }
    }
  }
  TSTAMP(threadIdx.x == 0, blockIdx.x * 80 + 2);
  const uint32_t xbar = rank == 2 ? B_V : B_QK;
  for (int s = 0; s < kNSeg; s++) {
    bool check = s > 0, pend = true, wpend = true;
    uint32_t ln, a3[16], bar0 = sb + B_MEM;
    float d[16];
    if (!R0 && s + 3 < kNSeg) mbar_wait(sb + B_XF + 8 * ((s + 1) & 1), ((s + 3) >> 1) & 1);
    while (true) {
      float c0[4], c1[4], c2[4], c3[4];
      uint32_t wx[16], b[16][4];
      ln = lane;
      OPAQUE(ln);
      {
        const uint32_t wr = sb + WRES + (warp >> 2) * 8192 + ((ln >> 4) * 8 + (ln & 7)) * 128 + (((2 * (warp & 3) + ((ln >> 3) & 1)) ^ (ln & 7)) << 4);
#pragma unroll
        for (int j = 0; j < 4; j++) ldsm4t(wr + j * 2048, wx[4 * j], wx[4 * j + 1], wx[4 * j + 2], wx[4 * j + 3]);
      }
      const uint32_t ma = sb + MEMS + ln * 16;
      const uint32_t dst = (R0 ? QM : KV + (rank - 1) * 10240 + 8192 + (s & 3) * 20480) + 256 * warp + 4 * ln;
      auto ldb = [&](int i) { ldsm4(ma + i * 512, b[i][0], b[i][1], b[i][2], b[i][3]); };
      auto mm = [&](int i) {
        if (CH4 && i == 12) {
          mma16z(c2, w[8 * i], w[8 * i + 1], w[8 * i + 2], w[8 * i + 3], b[i][0], b[i][1]);
          mma16z(c3, w[8 * i + 4], w[8 * i + 5], w[8 * i + 6], w[8 * i + 7], b[i][2], b[i][3]);
        } else {
          mma16(CH4 && !(i & 1) ? c2 : c0, w[8 * i], w[8 * i + 1], w[8 * i + 2], w[8 * i + 3], b[i][0], b[i][1]);
          mma16(CH4 && !(i & 1) ? c3 : c1, w[8 * i + 4], w[8 * i + 5], w[8 * i + 6], w[8 * i + 7], b[i][2], b[i][3]);
        }
      };
      TMARKW(1, 9 + warp, wx[15]);
      mbar_wait(bar0, s & 1);
      ldb(14); ldb(15);
      mbar_wait(sb + B_MEM + 8, s & 1);
      ldb(12);
      TMARKD(warp == 0, 0, b[14][0]);
      mma16z(c0, wx[0], wx[1], wx[2], wx[3], b[14][0], b[14][1]);
      mma16z(c1, wx[4], wx[5], wx[6], wx[7], b[14][2], b[14][3]);
      ldb(13);
      bool rdy = mbar_try(sb + B_MEM + 16, s & 1);
      mma16(c0, wx[8], wx[9], wx[10], wx[11], b[15][0], b[15][1]);
      mma16(c1, wx[12], wx[13], wx[14], wx[15], b[15][2], b[15][3]);
      if (!rdy) mbar_wait(sb + B_MEM + 16, s & 1);
      ldb(0); ldb(1);
      mm(12); ldb(2);
      mm(13); ldb(3);
      rdy = mbar_try(sb + B_MEM + 24, s & 1);
      mm(0);
      if (!rdy) mbar_wait(sb + B_MEM + 24, s & 1);
#pragma unroll
      for (int i = 1; i < 12; i++) {
        if (i + 3 < 12) ldb(i + 3);
        mm(i);
      }
      if (CH4) {
#pragma unroll
        for (int i = 0; i < 4; i++) c0[i] += c2[i] + c3[i];
      }
      const float v0 = c0[0] + c1[0], v1 = c0[1] + c1[1];
      const uint32_t r0 = pack2(v0, v1), r1 = pack2(c0[2] + c1[2], c0[3] + c1[3]);
      const bool bad = check && pend && (v0 != v0 || v1 != v1);
      if (pend && !bad) {
#pragma unroll
        for (uint32_t d = 0; d < 2; d++) {
          const uint32_t base = mapa(sb, R0 ? 1 + d : d ? 0u : 3u - rank);
          st_async32(base + dst, r0, base + xbar);
          st_async32(base + dst + 128, r1, base + xbar);
        }
        sts32(sb + dst, r0);
        sts32(sb + dst + 128, r1);
      }
      const bool wbad = __any_sync(~0u, bad);
      if (ln == 0 && wpend && !wbad) mbar_arrive(sb + xbar);
      TMARKD(warp == 0, 1, r1);
      TMARKD(warp == 7, 12, r1);
      if (!R0) {
        if (kSplit) r_proj_issue(w, d, sb, s + 1, warp, 0, kSplit);
        const uint32_t woa = sb + WOS + (warp >> 2) * 8192 + (16 * (warp & 3) + (ln & 15)) * 128 + (((ln >> 4) ^ (ln & 7)) << 4);
#pragma unroll
        for (int kk = 0; kk < 4; kk++) ldsm4(woa ^ (kk << 5), a3[4 * kk], a3[4 * kk + 1], a3[4 * kk + 2], a3[4 * kk + 3]);
      }
      if (!bar_red_or(NB_P, 256, bad)) break;
      if (!R0 && kSplit) wg_wait<0>();
      pend = bad; wpend = wbad;
      TMARKV(warp == 0, 28, 1);
      const bool first = bar0 != sb + B_OK;
      bar0 = sb + B_OK;
      if (first) continue;
      check = false;
      const unsigned char* pp = g_pub + (((s - 1) & 1) * 32768 + (warp >> 1) * 8192 + (warp & 1) * 1024 + ln * 16);
      uint32_t x[8];
      int budget = 1 << 18;
      do {
        spend(budget);
        TMARKV(warp == 0, 28, 1000);
        ld_v4(pp, x[0], x[1], x[2], x[3]);
        ld_v4(pp + 512, x[4], x[5], x[6], x[7]);
      } while (__any_sync(~0u, max(max(max(x[0], x[1]), max(x[2], x[3])), max(max(x[4], x[5]), max(x[6], x[7]))) == ~0u));
      sts128(ma + warp * 1024, x[0], x[1], x[2], x[3]);
      sts128(ma + warp * 1024 + 512, x[4], x[5], x[6], x[7]);
      fence_async_smem();
      bar_sync(NB_P, 256);
    }
    TMARKD(warp == 0, 14, 0);
    if (R0) {
      if (s + 1 == kNSeg) break;
      if (s == 0) bar_sync(NB_TAB, 512);
      const uint32_t unit = head * 4 + (warp >> 1), so = (s & 1) * 32768;
      const unsigned char* mb = g_mail + (unit * 8192 + (lds32(sb + TABS + unit * 4) & 4096u) + (warp & 1) * 32 + (ln >> 4) * 256 + (ln & 3) * 64 + ((ln >> 2) & 3) * 8);
      unsigned char* pwp = g_pub + ((unit >> 5) * 8192 + (unit & 31) * 64 + (warp & 1) * 32 + so + (ln & 1) * 4096 + (ln >> 2) * 4);
      const uint32_t sel = (ln & 4) ? 0x3F800000u : 0x3F80u;
      const uint32_t tagm = (s & 1) ? 0u : ~0u;
      bar_sync(NB_M, 288);
      spin_gt_until(lds32(sb + TK_X));
      TMARKD(warp == 0, 16, 0);
      for (int budget = 1 << 18;;) {
        uint32_t x[8];
#pragma unroll
        for (int i = 0; i < 4; i++) ld_v2(mb + i * 512, x[2 * i], x[2 * i + 1]);
        TMARKD(warp == 0, 15, x[0]);
        TMARKD(warp == 0, 23, x[0] | x[2] | x[4] | x[6]);
        float c[4], e[4];
        mma16z(c, x[0], x[1], x[2], x[3], sel, sel);
        mma16z(e, x[4], x[5], x[6], x[7], sel, sel);
        const bool ok = !__any_sync(~0u, (lop3<0x7e>(x[0], tagm, x[2]) | lop3<0x7e>(x[4], tagm, x[6])) & 1u);
#pragma unroll
        for (int i = 0; i < 4; i++) c[i] += e[i];
        const bool hi = ln & 16;
        const float u0 = (hi ? c[2] : c[0]) + __shfl_xor_sync(~0u, hi ? c[0] : c[2], 16);
        const float u1 = (hi ? c[3] : c[1]) + __shfl_xor_sync(~0u, hi ? c[1] : c[3], 16);
        const uint32_t wv = pack2(u0, u1);
        asm volatile("{.reg .pred p; setp.ne.u32 p, %2, 0; @p st.relaxed.gpu.global.u32 [%0], %1;}" ::"l"(pwp), "r"(wv), "r"((uint32_t)(ok && !(ln & 2))) : "memory");
        if (ok) { TMARKD(warp == 0, 9, wv); TMARKV(warp < 2, 24 + warp, (1 << 18) - budget); break; }
        spend(budget);
      }
      sts32(sb + TK + 16 + warp * 4, gtime());
      if (ln == 0) mbar_arrive(sb + B_PUB);
      if (!(ln & 2)) st_u32(pwp + (32768 - 2 * (int)so), ~0u);
      if (s + 2 == kNSeg) continue;
      mbar_wait(sb + B_XF + 8 * (s & 1), ((s + 2) >> 1) & 1);
      if (lds32(sb + TK_Q + (s & 1) * 4)) continue;
      mbar_wait(sb + B_PUB, s & 1);
      r_proj_issue(w, d, sb, s, warp, 0, 32);
    } else {
      uint32_t b[8];
      float c0[4], c1[4];
      const uint32_t va = sb + ln * 16 + (KV + 10240 + 8192) + (s & 3) * 20480 + (warp >> 2) * 1024;
      mbar_wait(sb + B_V, s & 1);
      ldsm4t(va, b[0], b[1], b[2], b[3]);
      ldsm4t(va + 512, b[4], b[5], b[6], b[7]);
      mma16z(c0, a3[0], a3[1], a3[2], a3[3], b[0], b[1]);
      mma16z(c1, a3[4], a3[5], a3[6], a3[7], b[2], b[3]);
      mma16(c0, a3[8], a3[9], a3[10], a3[11], b[4], b[5]);
      mma16(c1, a3[12], a3[13], a3[14], a3[15], b[6], b[7]);
      sts64(sb + ln * 16 + (VM + 4096) + (warp & 3) * 512 + (warp >> 2) * 8, pack2(c0[0] + c1[0], c0[1] + c1[1]), pack2(c0[2] + c1[2], c0[3] + c1[3]));
      bar_arrive(NB_S, 480);
      TMARKD(warp == 0, 18, 0);
      bar_sync(NB_TD, 384);
      TMARKD(warp == 1, 22, 0);
      r_proj_issue(w, d, sb, s + 1, warp, kSplit, 32);
    }
    wg_wait<0>();
    TMARKD(warp == 0, 7, __float_as_uint(d[0]));
    r_proj_store<R0>(d, sb, s + LA, warp, ln, rank);
    TMARKD(warp == 0, 2, 0);
  }
}

__global__ void __cluster_dims__(3, 1, 1) __launch_bounds__(512, 1)
recur_kernel(const __grid_constant__ CUtensorMap tmX, const __grid_constant__ CUtensorMap tmWq,
             const __grid_constant__ CUtensorMap tmWk, const __grid_constant__ CUtensorMap tmWv,
             const bf16* __restrict__ mem0, const bf16* __restrict__ Wo) {
  using namespace rk;
  extern __shared__ unsigned char smem_raw[];
  const uint32_t sb = (smem_u32(smem_raw) + 1023u) & ~1023u;
  const int warp = __shfl_sync(~0u, threadIdx.x >> 5, 0), lane = threadIdx.x & 31;
  const uint32_t rank = blockIdx.x % 3u, head = blockIdx.x / 3u;
  asm volatile("griddepcontrol.launch_dependents;");

  if (threadIdx.x == 256) {
    for (int i = 0; i < 4; i++) mbar_init(sb + B_W + 8 * i, 1);
    for (int i = 0; i < 2; i++) mbar_init(sb + B_XF + 8 * i, 1);
    asm volatile("fence.mbarrier_init.release.cluster;" ::: "memory");
    const CUtensorMap* tw = rank == 0 ? &tmWq : rank == 1 ? &tmWk : &tmWv;
    for (int c = 0; c < 4; c++) {
      mbar_arrive_tx(sb + B_W + 8 * c, 32768);
      for (int i = 0; i < 4; i++) {
        const int kb = 2 * c + (i >> 1), nb = i & 1;
        tma_2d(sb + RA + (kb * 2 + nb) * 8192, tw, head * 128 + nb * 64, kb * 64, sb + B_W + 8 * c);
      }
    }
    for (int st = 0; st < 2; st++) {
      mbar_arrive_tx(sb + B_XF + 8 * st, 32768);
      tma_3d(sb + XT + st * 32768, &tmX, 0, st * 32, 0, sb + B_XF + 8 * st);
    }
    if (blockIdx.x < 2) asm volatile("cp.async.bulk.prefetch.tensor.3d.L2.global [%0, {0, %1, 0}];" ::"l"(&tmX), "r"(64 + 32 * blockIdx.x) : "memory");
  }
  if (threadIdx.x == 288) {
    for (int i = 0; i < 4; i++) { mbar_init(sb + B_KV + 8 * i, 1); mbar_init(sb + B_MEM + 8 * i, 1); mbar_init(sb + B_Q + 8 * i, 1); mbar_init(sb + B_FIX + 8 * i, 1); }
    mbar_init(sb + B_QK, rank == 2 ? 1 : 9);
    mbar_init(sb + B_V, rank == 2 ? 9 : 1);
    mbar_init(sb + B_FREE, 24);
    mbar_init(sb + B_OF, 4);
    mbar_init(sb + B_PUB, rank == 0 ? 8 : 4);
    mbar_init(sb + B_OK, 1);
    mbar_arrive_tx(sb + B_QK, rank == 2 ? 4096 : 2048);
    mbar_arrive_tx(sb + B_V, rank == 2 ? 0 : 2048);
    for (int i = 0; i < 4; i++) mbar_arrive(sb + B_MEM + 8 * i);
    asm volatile("fence.mbarrier_init.release.cluster;" ::: "memory");
  }
  __syncwarp();
  asm volatile("barrier.cluster.arrive.relaxed.aligned;" ::: "memory");

  if (warp < 8) {
    asm volatile("setmaxnreg.inc.sync.aligned.u32 160;");
#pragma unroll
    for (int i = 0; i < 2; i++) {
      const int idx = threadIdx.x + i * 256;
      const uint4 v = __ldg(reinterpret_cast<const uint4*>(mem0 + (idx & 7) * kD + (idx >> 3) * 8));
      sts128(sb + MEMS + idx * 16, v.x, v.y, v.z, v.w);
    }
    cluster_wait();
    if (rank == 0) r_proj_role<true>(sb, warp, lane, rank, head, &tmX);
    else r_proj_role<false>(sb, warp, lane, rank, head, &tmX);
  } else if (warp < 12) {
    asm volatile("setmaxnreg.inc.sync.aligned.u32 136;");
    if (rank == 0) r_attn_role<2>(sb, warp - 8, lane, rank, head, Wo);
    else r_attn_role<3>(sb, warp - 8, lane, rank, head, Wo);
  } else {
    asm volatile("setmaxnreg.dec.sync.aligned.u32 56;");
    const int mw = warp - 12;
    const uint32_t unit = head * 4 + mw;
    const uint32_t pwo = (unit >> 5) * 8192 + (unit & 31) * 64;
    if (rank == 0) {
#pragma unroll
      for (int i = 0; i < 8; i++) st_b128(g_mail + unit * 8192 + (i >> 2) * 4096 + (i & 3) * 512 + lane * 16, 0u, 0u, 0u, 0u);
      st_v2(g_pub + pwo + (lane >> 4) * 32768 + ((lane >> 3) & 1) * 4096 + (lane & 7) * 8, ~0u, ~0u);
    }
    const uint32_t bit = (head * 6 + rank * 3 + mw) & 7;
    uint32_t ba = ~0u, bb = ~0u;
    cluster_wait();
    if (lane == 0) {
      const uint32_t pair = rank == 0 ? unit : (blockIdx.x & 7) ^ (mw < 3 ? 1u << bit : 0u);
      probe_pages(sb + B_W + 24, g_mail + pair * 8192 + 2048 + (blockIdx.x >> 3) * 128 + mw * 32 + (blockIdx.x & 7) * 4, ba, bb);
      asm volatile("st.shared.u8 [%0], %1;" ::"r"(sb + TK_PG + mw), "r"(min(bb - ba, 254u) + 1) : "memory");
    }
    TSTAMP(mw == 3 && lane == 0, blockIdx.x * 80 + 74);
    if (rank == 0) asm volatile("fence.acq_rel.gpu;" ::: "memory");
    __syncwarp();
    bar_sync(NB_X, 128);
    if (lane == 0) {
      const uint32_t dd = lds32v(sb + TK_PG);
      if (rank == 0 && mw == 3) st_u32(&g_tab[head], dd);
      if (rank && mw < 3) atomicAdd(&g_tab[32 + bit], (dd >> 24 > 80) != (bb - ba >= 80) ? 0x101u : 1u);
    }
    __syncwarp();
    if (mw == 3 && lane < 16) sts32(sb + TK + lane * 4, lane < 14 ? gtime() : 0u);
    {
      uint32_t u, z;
      int budget = 1 << 20;
      do {
        spend(budget);
        u = ld_acq(&g_tab[lane]); z = ld_u32(&g_tab[32 + (lane & 7)]);
      } while (__any_sync(~0u, !u || (z & 255u) != 24));
      const uint32_t mask = __ballot_sync(~0u, z >> 8 > 12) & 255u;
      int score = 0;
#pragma unroll
      for (int j = 0; j < 4; j++) {
        const int dj = (int)((u >> (8 * j)) & 255u) - 80;
        score += (__popc((lane * 4 + j) & mask) & 1) ? -dj : dj;
      }
      const uint32_t sides = __ballot_sync(~0u, score <= 0);
      const uint32_t un = mw * 32 + lane;
      sts32(sb + TABS + un * 4, ((__popc(un & mask) ^ (sides >> (un >> 2))) & 1u) << 12);
      bar_sync(NB_X, 128);
      if (mw == 3 && lane < 8) sts32(sb + TK_PG + lane * 4, ((__popc((128 + lane) & mask) ^ (sides >> head)) & 1u) << 12);
    }
    TSTAMP(mw == 0 && lane == 0, blockIdx.x * 80 + 4);
    __syncwarp();
    bar_arrive(NB_TAB, rank == 0 ? 512 : 256);
    TSTAMP(mw == 0 && lane == 0, blockIdx.x * 80 + 5);
    if (mw == 3) {
      r_timer_role(sb, lane, rank == 0);
    } else if (mw == 2) r_mscore_role(sb, lane, rank, head, &tmX);
    else r_score_role(sb, mw, lane, rank == 0 ? 224 : 480);
  }
  cluster_sync_all();
}

#define GST(e)
#define CST(e, v)
#define GSV(e, v)
#define PSL0 20
#define PSL1 1000
#define PD0 1600
#define PD1 450
namespace gk {
constexpr int kCtas = 36, kStages = 4;
constexpr uint32_t STG = 49152;
constexpr uint32_t EPI = kStages * STG;
constexpr uint32_t BAR = EPI + 32768;
constexpr uint32_t INFO = BAR + 64;
constexpr uint32_t AUX = INFO + 16;
constexpr uint32_t SMEM = AUX + 64 + 1024;
constexpr int kQ = 240, kF1 = 224, kF2 = 32;
constexpr int kWhole = kS0 / 4;
constexpr int kWo = 2 * kWhole;
constexpr int kUnits = kQ + kF1 + kF2 + kWo;
constexpr uint32_t kDraws = kUnits + kCtas;
constexpr int NB_EPI = 1, NB_DEP = 3, NB_LAG = 5;
#define LAGK 2
constexpr uint32_t kWoFirst = 31;
__device__ const unsigned short kOrder[kUnits] = {
  12, 140, 268, 396, 524, 652, 780, 908, 1036, 1164, 1292, 1420, 1548, 1676, 1804, 1932, 20, 148, 276, 404, 532, 660, 788, 916,
  1044, 1172, 1300, 1428, 1556, 1684, 1812, 1940, 120, 248, 376, 504, 632, 760, 888, 1016, 1144, 1272, 1400, 1528, 1656, 1784, 112, 240,
  368, 496, 624, 752, 880, 1008, 1136, 1264, 1392, 1520, 1648, 1776, 104, 232, 360, 488, 616, 744, 872, 1000, 1128, 1256, 1384, 1512,
  28, 156, 284, 412, 540, 668, 796, 924, 1052, 1180, 1308, 1436, 1564, 1692, 1820, 1948, 1640, 1768, 96, 224, 352, 480, 608, 736,
  864, 992, 1120, 1248, 1376, 1504, 1632, 1760, 88, 216, 344, 472, 36, 164, 292, 420, 548, 676, 804, 932, 1060, 1188, 1316, 1444,
  1572, 1700, 1828, 1956, 2, 130, 121, 249, 113, 241, 600, 728, 856, 984, 1112, 1240, 1368, 1496, 1624, 1752, 80, 208, 336, 464,
  592, 720, 848, 976, 1104, 1232, 1360, 1488, 1616, 1744, 72, 200, 328, 456, 584, 712, 840, 968, 1096, 1224, 1352, 1480, 1608, 1736,
  64, 192, 320, 448, 576, 704, 44, 172, 300, 428, 556, 684, 812, 940, 1068, 1196, 1324, 1452, 1580, 1708, 1836, 1964, 10, 138,
  832, 960, 1088, 1216, 1344, 1472, 1600, 1728, 56, 184, 312, 440, 52, 180, 308, 436, 564, 692, 820, 948, 1076, 1204, 1332, 1460,
  1588, 1716, 1844, 1972, 18, 146, 568, 696, 824, 952, 1080, 1208, 1336, 1464, 1592, 1720, 105, 233, 97, 225, 48, 176, 304, 432,
  560, 688, 816, 944, 1072, 1200, 1328, 1456, 1584, 1712, 40, 168, 296, 424, 552, 680, 808, 936, 1064, 1192, 1320, 1448, 60, 188,
  316, 444, 572, 700, 828, 956, 1084, 1212, 1340, 1468, 1596, 1724, 1852, 1980, 26, 154, 1576, 1704, 32, 160, 288, 416, 544, 672,
  68, 196, 324, 452, 580, 708, 836, 964, 1092, 1220, 1348, 1476, 1604, 1732, 1860, 1988, 34, 162, 800, 928, 1056, 1184, 1312, 1440,
  89, 217, 81, 209, 1568, 1696, 24, 152, 280, 408, 536, 664, 792, 920, 1048, 1176, 1304, 1432, 1560, 1688, 16, 144, 272, 400,
  528, 656, 76, 204, 332, 460, 588, 716, 844, 972, 1100, 1228, 1356, 1484, 1612, 1740, 1868, 1996, 42, 170, 784, 912, 1040, 1168,
  1296, 1424, 1552, 1680, 84, 212, 340, 468, 596, 724, 852, 980, 1108, 1236, 1364, 1492, 1620, 1748, 1876, 2004, 50, 178, 8, 136,
  264, 392, 520, 648, 776, 904, 1032, 1160, 1288, 1416, 1544, 1672, 0, 128, 256, 384, 512, 640, 768, 896, 1024, 1152, 73, 201,
  65, 193, 1280, 1408, 92, 220, 348, 476, 604, 732, 860, 988, 1116, 1244, 1372, 1500, 1628, 1756, 1884, 2012, 58, 186, 1536, 1664,
  57, 185, 49, 177, 41, 169, 33, 161, 100, 228, 356, 484, 612, 740, 868, 996, 1124, 1252, 1380, 1508, 1636, 1764, 1892, 2020,
  66, 194, 25, 153, 17, 145, 9, 137, 1, 129, 108, 236, 364, 492, 620, 748, 876, 1004, 1132, 1260, 1388, 1516, 1644, 1772,
  1900, 2028, 116, 244, 372, 500, 628, 756, 884, 1012, 1140, 1268, 1396, 1524, 1652, 1780, 1908, 2036, 124, 252, 380, 508, 636, 764,
  892, 1020, 1148, 1276, 1404, 1532, 1660, 1788, 1916, 2044,
};
}

__device__ __forceinline__ void wgmma_256(float (&d)[128], uint64_t adesc, uint64_t bdesc, int acc) {
  asm volatile("{.reg .pred p; setp.ne.b32 p, %130, 0;\n"
    "wgmma.mma_async.sync.aligned.m64n256k16.f32.bf16.bf16 {"
    "%0,%1,%2,%3,%4,%5,%6,%7,%8,%9,%10,%11,%12,%13,%14,%15,%16,%17,%18,%19,%20,%21,%22,%23,%24,%25,%26,%27,%28,%29,%30,%31,"
    "%32,%33,%34,%35,%36,%37,%38,%39,%40,%41,%42,%43,%44,%45,%46,%47,%48,%49,%50,%51,%52,%53,%54,%55,%56,%57,%58,%59,%60,%61,%62,%63,"
    "%64,%65,%66,%67,%68,%69,%70,%71,%72,%73,%74,%75,%76,%77,%78,%79,%80,%81,%82,%83,%84,%85,%86,%87,%88,%89,%90,%91,%92,%93,%94,%95,"
    "%96,%97,%98,%99,%100,%101,%102,%103,%104,%105,%106,%107,%108,%109,%110,%111,%112,%113,%114,%115,%116,%117,%118,%119,%120,%121,%122,%123,%124,%125,%126,%127"
    "}, %128, %129, p, 1, 1, 0, 1;}"
#define D8(i) "+f"(d[i]), "+f"(d[i + 1]), "+f"(d[i + 2]), "+f"(d[i + 3]), "+f"(d[i + 4]), "+f"(d[i + 5]), "+f"(d[i + 6]), "+f"(d[i + 7])
    : D8(0), D8(8), D8(16), D8(24), D8(32), D8(40), D8(48), D8(56), D8(64), D8(72), D8(80), D8(88), D8(96), D8(104), D8(112), D8(120)
#undef D8
    : "l"(adesc), "l"(bdesc), "r"(acc));
}
__device__ __forceinline__ void wait_count(const unsigned* p, uint32_t target, int& budget) {
  while ((int)(ld_acq(p) - target) < 0) { spend(budget); __nanosleep(64); }
}
__device__ __forceinline__ float sigmoidf_(float x) { float t; asm("tanh.approx.f32 %0, %1;" : "=f"(t) : "f"(0.5f * x)); return fmaf(t, 0.5f, 0.5f); }
__device__ __forceinline__ uint32_t add_bf2(uint32_t a, uint32_t b) { uint32_t r; asm("add.rn.bf16x2 %0, %1, %2;" : "=r"(r) : "r"(a), "r"(b)); return r; }

template <bool ADD>
__device__ __forceinline__ void g_store_out(const float (&d)[128], float s0, float s1, uint32_t stg, bf16* __restrict__ dst, int lane) {
  const uint32_t wa = stg + (lane & 15) * 256, wx = (lane >> 4) ^ (lane & 7);
#pragma unroll
  for (int h = 0; h < 2; h++) {
    uint4 prev[8];
    if (ADD) {
#pragma unroll
      for (int i = 0; i < 8; i++) prev[i] = __ldcg(reinterpret_cast<const uint4*>(dst + (2 * i + (lane >> 4)) * kD + h * 128 + (lane & 15) * 8));
    }
#pragma unroll
    for (int i = 0; i < 8; i++) {
      const float* p = d + 64 * h + 8 * i;
      stsm4(wa + (((2 * i) ^ wx) << 4), pack2(p[0] * s0, p[1] * s0), pack2(p[2] * s1, p[3] * s1), pack2(p[4] * s0, p[5] * s0), pack2(p[6] * s1, p[7] * s1));
    }
    __syncwarp();
#pragma unroll
    for (int i = 0; i < 8; i++) {
      const int row = 2 * i + (lane >> 4);
      uint4 v;
      lds128(stg + row * 256 + (((lane & 15) ^ (row & 7)) << 4), v.x, v.y, v.z, v.w);
      if (ADD) { v.x = add_bf2(v.x, prev[i].x); v.y = add_bf2(v.y, prev[i].y); v.z = add_bf2(v.z, prev[i].z); v.w = add_bf2(v.w, prev[i].w); }
      *reinterpret_cast<uint4*>(dst + row * kD + h * 128 + (lane & 15) * 8) = v;
    }
    __syncwarp();
  }
}

__global__ void __launch_bounds__(384, 1)
gemm_kernel(const __grid_constant__ CUtensorMap tmX, const __grid_constant__ CUtensorMap tmWg, const __grid_constant__ CUtensorMap tmWu,
            const __grid_constant__ CUtensorMap tmWd, const __grid_constant__ CUtensorMap tmWo, const __grid_constant__ CUtensorMap tmWq,
            const __grid_constant__ CUtensorMap tmWs,             const bf16* __restrict__ x, const bf16* __restrict__ gw, bf16* __restrict__ out) {
  using namespace gk;
  extern __shared__ unsigned char smem_raw[];
  const uint32_t sb = (smem_u32(smem_raw) + 1023u) & ~1023u;
  const int warp = __shfl_sync(~0u, threadIdx.x >> 5, 0), lane = threadIdx.x & 31;
  int budget = 1 << 20;
  TSTAMP(threadIdx.x == 0, (96 + blockIdx.x) * 80);
  if (threadIdx.x == 0) {
    for (int i = 0; i < kStages; i++) { mbar_init(sb + BAR + 8 * i, 1); mbar_init(sb + BAR + 32 + 8 * i, 2); }
    sts64(sb + AUX + 40, 0, 0);
    asm volatile("fence.mbarrier_init.release.cluster;" ::: "memory");
  }
  __syncthreads();

  if (warp < 4) {
    asm volatile("setmaxnreg.dec.sync.aligned.u32 104;");
    if (warp == 0) {
      if (lane == 0) {
        uint32_t it = 0;
        while (true) {
          const uint32_t tk = atomicAdd(&g_ticket, 1u);
          const uint32_t ep = tk / kDraws + 1;
          const uint32_t u = tk % kDraws;
          const uint32_t code = u < kUnits ? kOrder[u] : u < kUnits + 32 ? 5 | (u - kUnits) << 7 : 3;
          const int type = code & 7, rb = (code >> 3) & 15, nb = code >> 7;
          const int nk = type == 1 ? 28 : type == 2 ? 64 : type == 5 ? 4 : 8;
          if (it == 0) sts32(sb + AUX + 32, ep);
          const bf16* asrc = type == 1 ? g_hid + (size_t)rb * 28 * 8192 : g_o + (size_t)rb * 64 * 8192;
          const int pre = kStages;
          for (int k = 0; k < nk; k++) {
            const uint32_t st = (it + k) % kStages, ph = ((it + k) / kStages) & 1;
            const uint32_t full = sb + BAR + 8 * st, sa = sb + st * STG;
            mbar_wait(full + 32, ph ^ 1, budget);
            asm volatile("st.shared.u32 [%0], %1;" ::"r"(sb + INFO + 4 * st), "r"(code) : "memory");
            if (type == 3) { mbar_arrive(full); break; }
            mbar_arrive_tx(full, type == 5 ? 32768 : STG);
            if (type == 5) {
              tma_3d(sa + 16384, &tmWs, 0, (nb >> 2) * 512 + st * 128, (nb & 3) * 2, full);
            } else if (type == 0) {
              tma_2d(sa, &tmX, k * 64, rb * 128, full);
              tma_3d(sa + 16384, &tmWg, 0, k * 64, nb * 2, full);
              tma_3d(sa + 32768, &tmWu, 0, k * 64, nb * 2, full);
            } else if (type == 4) {
              tma_2d(sa, &tmX, k * 64, rb * 128, full);
              tma_3d(sa + 16384, &tmWq, 0, k * 64, nb * 4, full);
            } else {
              tma_3d(sa + 16384, type == 1 ? &tmWd : &tmWo, 0, k * 64, nb * 4, full);
              if (k >= pre) bulk_g2s(sa, asrc + k * 8192, 16384, full);
              else if (k == pre - 1) {
                if (type == 1) wait_count(&g_cnt[C_HID + rb], ep * 28, budget);
                else wait_count(&g_cnt[C_O + rb], ep * 128, budget);
                asm volatile("fence.proxy.async.global;" ::: "memory");
                for (int j = 0; j < pre; j++) bulk_g2s(sb + ((it + j) % kStages) * STG, asrc + j * 8192, 16384, sb + BAR + 8 * ((it + j) % kStages));
              }
            }
          }
          if (type == 5) {
            it += 4;
            for (int sg = kS0; sg < kNSeg; sg++, it++) {
              const uint32_t st = it % kStages, full = sb + BAR + 8 * st;
              const unsigned* cnt = &g_cnt[C_S + (sg - kS0) * 8 + (nb >> 2)];
              while ((int)(ld_acq(cnt) - 4 * ep) < 0) spend(budget);
              asm volatile("fence.proxy.async.global;" ::: "memory");
              mbar_wait(full + 32, ((it / kStages) & 1) ^ 1, budget);
              mbar_arrive_tx(full, 32768);
              const bf16* src = g_o + (size_t)((sg >> 2) * 64 + (nb >> 2) * 8) * 8192 + (sg & 3) * 2048;
#pragma unroll
              for (int j = 0; j < 8; j++) bulk_g2s(sb + st * STG + 16384 + j * 4096, src + j * 8192, 4096, full);
            }
          }
          if (type == 3 || type == 5) break;
          it += nk;
        }
      }
    } else if (warp < 3) {
      uint32_t idx, pad, lo, hi;
      while (true) {
        bar_sync(NB_EPI + warp - 1, 160);
        lds128(sb + AUX + 16 * (warp - 1), idx, pad, lo, hi);
        if (lane == 0 && (lo | hi)) {
          unsigned char* dst = reinterpret_cast<unsigned char*>((uint64_t)hi << 32 | lo);
          const uint32_t src = sb + EPI + (warp - 1) * 16384;
          bulk_s2g(dst, src, 8192);
          bulk_s2g(dst + 16384, src + 8192, 8192);
          asm volatile("cp.async.bulk.commit_group; cp.async.bulk.wait_group.read 0;" ::: "memory");
        }
        __syncwarp();
        bar_arrive(NB_DEP + warp - 1, 160);
        if (idx == ~0u) break;
        if (lane == 0 && idx != ~1u)
          asm volatile("cp.async.bulk.wait_group 0; fence.proxy.async.global; red.release.gpu.global.add.u32 [%0], 1;" ::"l"(&g_cnt[idx]) : "memory");
        __syncwarp();
      }
      if (pad < 32) {
        const uint32_t ep = lds32v(sb + AUX + 32), nq = pad & 3, kq = pad >> 2;
        const int col = nq * 128 + (warp - 1) * 64 + (lane >> 3) * 16 + (lane & 7) + (kq & 1) * 8;
        if (lane < (kNSeg - kS0) / 4) wait_count(&g_cnt[C_F2 + (kS0 / 4 + lane) * 2 + (nq >> 1)], 2 * ep, budget);
        __syncwarp();
        for (int sg = kS0; sg < kNSeg; sg++) {
          const int row = sg * 32 + (kq >> 1) * 8;
          unsigned short* dst = reinterpret_cast<unsigned short*>(out) + row * kD + col;
          uint32_t prev[8], gv[8];
          const uint32_t* src = g_part + (size_t)(((sg - kS0) * 4 + nq) * 8 + kq) * 2048 + (warp - 1) * 128 + lane * 4;
          float a[8];
          while (lds32v(sb + AUX + 36 + 4 * warp) <= sg) { spend(budget); __nanosleep(PSL0); }
          if (lds32v(sb + AUX + 36 + 4 * warp) == sg + 1) spin_clk_until(lds32v(sb + AUX + 44 + 4 * warp) + (sg + 1 < kNSeg ? PD0 : PD1));
          CST(0, gtime());
          for (int tries = 0;; tries++) {
            CST(2, tries);
            uint32_t v[32], bad = 0;
#pragma unroll
            for (int i = 0; i < 8; i++)
              asm volatile("ld.relaxed.gpu.global.v4.b32 {%0,%1,%2,%3}, [%4];"
                           : "=r"(v[4 * i]), "=r"(v[4 * i + 1]), "=r"(v[4 * i + 2]), "=r"(v[4 * i + 3]) : "l"(src + i * 256) : "memory");
#pragma unroll
            for (int i = 0; i < 8; i++) asm volatile("ld.relaxed.gpu.global.u16 %0, [%1];" : "=r"(prev[i]) : "l"(dst + i * kD) : "memory");
            ld_v4(g_gate + row, gv[0], gv[1], gv[2], gv[3]);
            ld_v4(g_gate + row + 4, gv[4], gv[5], gv[6], gv[7]);
#pragma unroll
            for (int i = 0; i < 8; i++) a[i] = 0.f;
#pragma unroll
            for (int i = 0; i < 32; i++) {
              bad |= v[i] ^ ep;
              a[(i & 3) * 2] += __uint_as_float((v[i] << 16) & 0xfffe0000u);
              a[(i & 3) * 2 + 1] += __uint_as_float(v[i] & 0xffff0000u);
            }
            if (!__any_sync(~0u, bad & 1)) break;
            spend(budget);
            if (sg + 1 < kNSeg) __nanosleep(PSL1);
          }
          CST(1, gtime());
#pragma unroll
          for (int i = 0; i < 8; i++) dst[i * kD] = (unsigned short)pack2(fmaf(a[i], __uint_as_float(gv[i]), __uint_as_float(prev[i] << 16)), 0.f);
        }
        TSTAMP(lane == 0, (96 + blockIdx.x) * 80 + 1);
      }
    } else if (blockIdx.x < 32) {
      float w[16];
#pragma unroll
      for (int i = 0; i < 2; i++) {
        const uint4 v = __ldg(reinterpret_cast<const uint4*>(gw + i * 256 + lane * 8));
        const uint32_t q[4] = {v.x, v.y, v.z, v.w};
#pragma unroll
        for (int j = 0; j < 4; j++) { w[8 * i + 2 * j] = __uint_as_float(q[j] << 16); w[8 * i + 2 * j + 1] = __uint_as_float(q[j] & 0xffff0000u); }
      }
      const int r0 = blockIdx.x * 64;
      for (int r = r0; r < r0 + 64; r++) {
        float a = 0.f;
#pragma unroll
        for (int i = 0; i < 2; i++) {
          const uint4 v = __ldg(reinterpret_cast<const uint4*>(x + r * kD + i * 256 + lane * 8));
          const uint32_t q[4] = {v.x, v.y, v.z, v.w};
#pragma unroll
          for (int j = 0; j < 4; j++) a = fmaf(__uint_as_float(q[j] << 16), w[8 * i + 2 * j], fmaf(__uint_as_float(q[j] & 0xffff0000u), w[8 * i + 2 * j + 1], a));
        }
#pragma unroll
        for (int o = 16; o; o >>= 1) a += __shfl_xor_sync(~0u, a, o);
        if (lane == 0) g_gate[r] = 1.f / (1.f + __expf(-a));
      }
      if (lane == 0) asm volatile("red.release.gpu.global.add.u32 [%0], 1;" ::"l"(&g_cnt[C_G + (blockIdx.x >> 1)]) : "memory");
    }
  } else {
    asm volatile("setmaxnreg.inc.sync.aligned.u32 200;");
    const int cw = warp - 4, ct = threadIdx.x - 128, wg = cw >> 2;
    const uint32_t stg = sb + EPI + cw * 4096;
    const uint32_t wa = sb + EPI + wg * 16384 + ((cw & 3) * 16 + (lane & 15)) * 128, wx = (lane >> 4) ^ (lane & 7);
    uint32_t it = 0;
    bool pending = false;
    float d[128];
    int un = 0;
    uint32_t role = 32, ep;
    while (true) {
      GST(0);
      mbar_wait(sb + BAR + 8 * (it % kStages), (it / kStages) & 1, budget);
      uint32_t code;
      asm volatile("ld.shared.u32 %0, [%1];" : "=r"(code) : "r"(sb + INFO + 4 * (it % kStages)) : "memory");
      const int type = code & 7, rb = (code >> 3) & 15, nb = code >> 7;
      ep = lds32(sb + AUX + 32);
      if (type == 5) role = nb;
      if (type == 3 || type == 5) break;
      TSTAMP(ct == 0, (96 + blockIdx.x) * 80 + 8 + 4 * rb + min(type, 3));
      const int nk = type == 1 ? 28 : type == 2 ? 64 : 8;
      GST(1);
      GST(2);
      for (int k = 0; k < nk; k++, it++) {
        const uint32_t st = it % kStages;
        if (k) mbar_wait(sb + BAR + 8 * st, (it / kStages) & 1, budget);
        if (wg ? k <= nk - LAGK : k >= LAGK) bar_sync(NB_LAG + wg, 256);
        const uint64_t ad = make_desc(sb + st * STG + (cw >> 2) * 8192, 16, 1024, 1);
        const uint64_t bd = make_desc(sb + st * STG + 16384, 8192, 1024, 1);
        wg_fence();
#pragma unroll
        for (int j = 0; j < 4; j++) wgmma_256(d, ad + (uint64_t)(2 * j), bd + (uint64_t)(128 * j), k | j);
        wg_commit();
        if (wg ? k < nk - LAGK : k >= LAGK - 1) bar_arrive(NB_LAG + 1 - wg, 256);
        wg_wait<1>();
        if (k && (ct & 127) == 0) mbar_arrive(sb + BAR + 32 + 8 * ((it - 1) % kStages));
      }
      if (pending) bar_sync(NB_DEP + wg, 160);
      pending = false;
      wg_wait<0>();
      GST(3);
      if ((ct & 127) == 0) mbar_arrive(sb + BAR + 32 + 8 * ((it - 1) % kStages));
      const int row = rb * 128 + cw * 16;
      uint32_t flag = ~1u;
      uint64_t tile_dst = 0;
      if (type == 0) {
#pragma unroll
        for (int i = 0; i < 8; i++) {
          float h[8];
#pragma unroll
          for (int j = 0; j < 8; j++) h[j] = sigmoidf_(d[8 * i + j]) * d[64 + 8 * i + j];
          stsm4(wa + (i >> 2) * 8192 + (((2 * (i & 3)) ^ wx) << 4), pack2(h[0], h[1]), pack2(h[2], h[3]), pack2(h[4], h[5]), pack2(h[6], h[7]));
        }
        fence_async_smem();
        tile_dst = (uint64_t)(g_hid + (size_t)(rb * 28 + nb * 2) * 8192 + wg * 4096);
        flag = C_HID + rb;
      } else if (type == 4) {
        tile_dst = (uint64_t)(g_q + (size_t)(rb * 64 + nb * 4) * 8192 + wg * 4096);
#pragma unroll
        for (int i = 0; i < 8; i++) {
          const float* p = d + 8 * i;
          stsm4(wa + (i >> 2) * 8192 + (((2 * (i & 3)) ^ wx) << 4), pack2(p[0], p[1]), pack2(p[2], p[3]), pack2(p[4], p[5]), pack2(p[6], p[7]));
        }
        fence_async_smem();
        if ((ct & 127) == 0) sts128(sb + AUX + 16 * wg, ~1u, 0, (uint32_t)tile_dst, (uint32_t)(tile_dst >> 32));
        bar_arrive(NB_EPI + wg, 160);
        uint32_t pk[32];
#pragma unroll
        for (int i = 0; i < 32; i++) pk[i] = pack2(d[64 + 2 * i], d[65 + 2 * i]);
        bar_sync_after(NB_DEP + wg, 160, pk[0] | pk[9] | pk[18] | pk[31], 0);
#pragma unroll
        for (int i = 0; i < 8; i++) stsm4(wa + (i >> 2) * 8192 + (((2 * (i & 3)) ^ wx) << 4), pk[4 * i], pk[4 * i + 1], pk[4 * i + 2], pk[4 * i + 3]);
        fence_async_smem();
        tile_dst += 32768;
        flag = C_Q + rb * 16 + nb;
      } else {
        const int tile = rb * 2 + nb;
        const bool first = (type == 2) == ((kWoFirst >> rb) & 1);
        bf16* dst = out + row * kD + nb * 256;
        if (lane == 0) wait_count(&g_cnt[first ? C_G + rb : C_F2 + tile], 2 * ep, budget);
        __syncwarp();
        float g0 = __ldcg(&g_gate[row + (lane >> 2)]), g1 = __ldcg(&g_gate[row + 8 + (lane >> 2)]);
        if (type == 1) { g0 = 1.f - g0; g1 = 1.f - g1; }
        if (first) {
          g_store_out<false>(d, g0, g1, stg, dst, lane);
          flag = C_F2 + tile;
        } else {
          g_store_out<true>(d, g0, g1, stg, dst, lane);
        }
      }
      GST(4);
      GSV(5, code);
      un++;
      if (flag != ~1u) {
        if ((ct & 127) == 0) sts128(sb + AUX + 16 * wg, flag, 0, (uint32_t)tile_dst, (uint32_t)(tile_dst >> 32));
        bar_arrive(NB_EPI + wg, 160);
        pending = true;
      }
    }
    TSTAMP(ct == 128, (96 + blockIdx.x) * 80 + 4);
    if (pending) bar_sync(NB_DEP + wg, 160);
    if ((ct & 127) == 0) sts128(sb + AUX + 16 * wg, ~0u, role, 0, 0);
    bar_arrive(NB_EPI + wg, 160);
    bar_sync(NB_DEP + wg, 160);
    if (role < 32) {
      for (int k = 1; k < 4; k++) mbar_wait(sb + BAR + 8 * ((it + k) % kStages), ((it + k) / kStages) & 1, budget);
      uint32_t w[128];
      const uint32_t wl = sb + 16384 + wg * 16384 + ((lane >> 4) * 8 + (lane & 7)) * 128 + (((2 * (cw & 3) + ((lane >> 3) & 1)) ^ (lane & 7)) << 4);
#pragma unroll
      for (int j = 0; j < 32; j++) ldsm4t(wl + (j >> 3) * STG + (j & 7) * 2048, w[4 * j], w[4 * j + 1], w[4 * j + 2], w[4 * j + 3]);
      bar_sync_after(NB_LAG + wg, 128, w[127], 0);
      if ((ct & 127) < 4) mbar_arrive(sb + BAR + 32 + 8 * (ct & 3));
      it += 4;
      uint32_t* dst = g_part + (size_t)(role & 3) * 16384 + (role >> 2) * 256 + ct;
      for (int sg = 0; sg < kNSeg - kS0; sg++, it++) {
        float c[16];
        const uint32_t st = it % kStages;
        const uint64_t bd = make_desc(sb + st * STG + 16384, 16, 1024, 1);
        mbar_wait(sb + BAR + 8 * st, (it / kStages) & 1, budget);
        TSTAMP(ct == 0 && sg + kS0 == 63, (96 + blockIdx.x) * 80 + 2);
        wg_fence();
#pragma unroll
        for (int j = 0; j < 32; j++) wgmma_rs32<0>(c, w[4 * j], w[4 * j + 1], w[4 * j + 2], w[4 * j + 3], bd + (uint64_t)(((j >> 2) * 4096 + (j & 3) * 32) >> 4), j > 0);
        wg_commit();
        wg_wait<0>();
#pragma unroll
        for (int i = 0; i < 8; i++)
          asm volatile("st.relaxed.gpu.global.b32 [%0], %1;"
                       ::"l"(dst + (size_t)sg * 65536 + i * 2048), "r"(pack2(0.f, c[2 * i + 1]) | (((__float_as_uint(c[2 * i]) + 0x10000u) >> 16) & 0xfffeu) | (ep & 1)) : "memory");
        if ((ct & 127) == 0) { mbar_arrive(sb + BAR + 32 + 8 * st); sts32(sb + AUX + 48 + 4 * wg, clk()); sts32(sb + AUX + 40 + 4 * wg, kS0 + sg + 1); }
        TSTAMP(ct == 128 && sg + kS0 == 63, (96 + blockIdx.x) * 80 + 3);
      }
    }
  }
}

typedef CUresult (*EncodeFn)(CUtensorMap*, CUtensorMapDataType, cuuint32_t, void*, const cuuint64_t*, const cuuint64_t*,
                             const cuuint32_t*, const cuuint32_t*, CUtensorMapInterleave, CUtensorMapSwizzle,
                             CUtensorMapL2promotion, CUtensorMapFloatOOBfill);

static void make_map(EncodeFn fn, CUtensorMap* m, const void* base, uint64_t cols, uint64_t rows, uint32_t bc, uint32_t br) {
  cuuint64_t dims[2] = {cols, rows};
  cuuint64_t strides[1] = {cols * 2};
  cuuint32_t box[2] = {bc, br};
  cuuint32_t es[2] = {1, 1};
  fn(m, CU_TENSOR_MAP_DATA_TYPE_BFLOAT16, 2, const_cast<void*>(base), dims, strides, box, es, CU_TENSOR_MAP_INTERLEAVE_NONE,
     CU_TENSOR_MAP_SWIZZLE_128B, CU_TENSOR_MAP_L2_PROMOTION_L2_256B, CU_TENSOR_MAP_FLOAT_OOB_FILL_NONE);
}

static void make_map3(EncodeFn fn, CUtensorMap* m, const void* base, uint64_t cols, uint64_t rows, uint32_t br, uint32_t nc) {
  cuuint64_t dims[3] = {64, rows, cols / 64};
  cuuint64_t strides[2] = {cols * 2, 128};
  cuuint32_t box[3] = {64, br, nc};
  cuuint32_t es[3] = {1, 1, 1};
  fn(m, CU_TENSOR_MAP_DATA_TYPE_BFLOAT16, 3, const_cast<void*>(base), dims, strides, box, es, CU_TENSOR_MAP_INTERLEAVE_NONE,
     CU_TENSOR_MAP_SWIZZLE_128B, CU_TENSOR_MAP_L2_PROMOTION_L2_256B, CU_TENSOR_MAP_FLOAT_OOB_FILL_NONE);
}

extern "C" void kernel_launch(void* const* d_in, const int* in_sizes, int n_in, void* d_out, int out_size) {
  const bf16* x = (const bf16*)d_in[0];
  const bf16* mem0 = (const bf16*)d_in[1];
  const bf16* Wo = (const bf16*)d_in[5];
  void* fp = nullptr;
  cudaDriverEntryPointQueryResult qr;
  cudaGetDriverEntryPoint("cuTensorMapEncodeTiled", &fp, cudaEnableDefault, &qr);
  EncodeFn fn = (EncodeFn)fp;
  CUtensorMap tmX, tmWq, tmWk, tmWv;
  make_map3(fn, &tmX, x, kD, kS, 32, 8);
  make_map(fn, &tmWq, d_in[2], 4096, kD, 64, 64);
  make_map(fn, &tmWk, d_in[3], 4096, kD, 64, 64);
  make_map(fn, &tmWv, d_in[4], 4096, kD, 64, 64);
  cudaFuncSetAttribute(recur_kernel, cudaFuncAttributeMaxDynamicSharedMemorySize, rk::SMEM);
  recur_kernel<<<96, 512, rk::SMEM>>>(tmX, tmWq, tmWk, tmWv, mem0, Wo);
  CUtensorMap tmX2, tmWg, tmWu, tmWd, tmWo, tmWq2, tmWs;
  make_map(fn, &tmX2, x, kD, kS, 64, 128);
  make_map3(fn, &tmWg, d_in[8], kF, kD, 64, 2);
  make_map3(fn, &tmWu, d_in[9], kF, kD, 64, 2);
  make_map3(fn, &tmWd, d_in[10], kD, kF, 64, 4);
  make_map3(fn, &tmWo, Wo, kD, 4096, 64, 4);
  make_map3(fn, &tmWs, Wo, kD, 4096, 128, 2);
  make_map3(fn, &tmWq2, d_in[2], 4096, kD, 64, 4);
  cudaFuncSetAttribute(gemm_kernel, cudaFuncAttributeMaxDynamicSharedMemorySize, gk::SMEM);
  cudaLaunchConfig_t cfg = {};
  cfg.gridDim = dim3(gk::kCtas);
  cfg.blockDim = dim3(384);
  cfg.dynamicSmemBytes = gk::SMEM;
  cfg.stream = cudaStreamPerThread;
  cudaLaunchAttribute at[1];
  at[0].id = cudaLaunchAttributeProgrammaticStreamSerialization;
  at[0].val.programmaticStreamSerializationAllowed = 1;
  cfg.attrs = at;
  cfg.numAttrs = 1;
  cudaLaunchKernelEx(&cfg, gemm_kernel, tmX2, tmWg, tmWu, tmWd, tmWo, tmWq2, tmWs, x, (const bf16*)d_in[11], (bf16*)d_out);
}
```
